```python
import torch

def _softmax(x, axis=-1):
    return torch.softmax(x, dim=axis)
def _gelu(x):
    return torch.nn.functional.gelu(x, approximate="tanh")
def _silu(x):
    return torch.nn.functional.silu(x)
def _sigmoid(x):
    return torch.sigmoid(x)
def _layernorm(x, axis=-1, eps=1e-5):
    m = x.mean(dim=axis, keepdim=True)
    v = x.var(dim=axis, keepdim=True, unbiased=False)
    return (x - m) / torch.sqrt(v + eps)
def _scatter_add(tgt, idx, src, axis=0):
    return tgt.clone().index_add_(axis, idx, src)
def _segment_sum(src, seg, n):
    out = torch.zeros((n,) + src.shape[1:], dtype=src.dtype)
    return out.index_add_(0, seg, src)
def _pad(x, pw):
    flat = tuple(v for pair in reversed(pw) for v in pair)
    return torch.nn.functional.pad(x, flat)

kernel_name = 'recurrent_scan__ssm_conv_s4d__mixer_channel_mlp__prompt'

def setup_inputs():

    _w = (lambda a: (lambda t: t.to(torch.bfloat16) if t.is_floating_point() else t)(torch.as_tensor(a)))
    def _A_setup():
        Bsz, L, D, N = 1, 2048, 448, 256
        return {
            "u": _w((lambda *s: torch.randn(*s, dtype=torch.bfloat16) * 0.05)(Bsz, L, D)),
            "log_A_real": _w((lambda *s: torch.randn(*s, dtype=torch.bfloat16) * 3.2)(D, N) * 0.5),
            "A_imag": _w((lambda *s: torch.randn(*s, dtype=torch.bfloat16) * 0.2)(D, N) * 3.14),
            "C_real": _w((lambda *s: torch.randn(*s, dtype=torch.bfloat16) * 0.8)(D, N) / N ** 0.5),
            "C_imag": _w((lambda *s: torch.randn(*s, dtype=torch.bfloat16) * 0.8)(D, N) / N ** 0.5),
            "log_dt": _w((lambda *s: torch.randn(*s, dtype=torch.bfloat16) * 0.2)(D) * 0.5 - 4.0),
            "D_skip": _w((lambda *s: torch.randn(*s, dtype=torch.bfloat16) * 0.2)(D)),
        }
    _A_in = _A_setup()

    def _B_setup():
        B, S, D, F = 1, 2048, 448, 1792
        return {
            "x": _w((lambda *s: torch.randn(*s, dtype=torch.bfloat16) * 0.05)(B, S, D)),
            "w1": _w((lambda *s: torch.randn(*s, dtype=torch.bfloat16) * 1.6)(D, F) * (D ** -0.5)),
            "b1": _w((lambda *s: torch.randn(*s, dtype=torch.bfloat16) * 0.8)(F)),
            "w2": _w((lambda *s: torch.randn(*s, dtype=torch.bfloat16) * 0.1)(F, D) * (F ** -0.5)),
            "b2": _w((lambda *s: torch.randn(*s, dtype=torch.bfloat16) * 0.1)(D)),
        }
    _B_in = _B_setup()

    return {
        "A_u": _A_in["u"],
        "A_log_A_real": _A_in["log_A_real"],
        "A_A_imag": _A_in["A_imag"],
        "A_C_real": _A_in["C_real"],
        "A_C_imag": _A_in["C_imag"],
        "A_log_dt": _A_in["log_dt"],
        "A_D_skip": _A_in["D_skip"],
        "B_x": _B_in["x"],
        "B_w1": _B_in["w1"],
        "B_b1": _B_in["b1"],
        "B_w2": _B_in["w2"],
        "B_b2": _B_in["b2"],
    }

def reference(A_u, A_log_A_real, A_A_imag, A_C_real, A_C_imag, A_log_dt, A_D_skip, B_x, B_w1, B_b1, B_w2, B_b2):
    def _A_ref(u, log_A_real, A_imag, C_real, C_imag, log_dt, D_skip):
        L = u.shape[1]
        dt = torch.exp(log_dt)
        A = -torch.exp(log_A_real) + 1j * A_imag
        C = (C_real + 1j * C_imag) * dt[:, None]
        pos = (lambda x, dt: x.to(dt))(torch.arange(L), log_dt.dtype)
        P = torch.exp((A * dt[:, None])[:, :, None] * pos[None, None, :])
        K = 2.0 * torch.einsum("dn,dnl->dl", C, P).real
        L2 = 2 * L
        u_t = (lambda x, *d: x.permute(*d))(u, 0, 2, 1)
        Kf = (lambda x, *a, **k: torch.fft.rfft(x.float(), *a, **k))(K, L2)
        Uf = (lambda x, *a, **k: torch.fft.rfft(x.float(), *a, **k))(u_t, L2)
        y = (lambda x, *a, **k: torch.fft.irfft(x, *a, **k).to(torch.bfloat16))(Uf * Kf[None, :, :], L2)[:, :, :L]
        y = (lambda x, *d: x.permute(*d))(y, 0, 2, 1)
        return y + u * D_skip[None, None, :]

    def _B_ref(x, w1, b1, w2, b2):
        y = _layernorm(x, axis=-1)
        h = _gelu(torch.einsum("bsd,df->bsf", y, w1) + b1)
        return torch.einsum("bsf,fd->bsd", h, w2) + b2

    x = A_u
    xn = _layernorm(x, axis=-1)
    s = _A_ref(xn, A_log_A_real, A_A_imag, A_C_real, A_C_imag, A_log_dt, A_D_skip)
    g = _silu(_B_ref(xn, B_w1, B_b1, B_w2, B_b2))
    return x + s * g
```

```cpp
#include <cuda_runtime.h>
#include <cuda_bf16.h>
#include <cuda_fp16.h>
#include <cuda.h>
#include <stdint.h>

namespace {

constexpr int SEQ = 2048, DM = 448, FF = 1792, NS = 256;
constexpr int NCTA = 128, NTHR = 384;

__device__ __align__(128) __half g_xnT[DM * SEQ];
__device__ __align__(128) float4 g_stats[SEQ];
__device__ __align__(128) float g_cs[FF];
__device__ __align__(128) uint2 g_y[DM * 16 * 32];
__device__ __align__(128) uint4 g_part[16 * 8 * 8 * 4 * 256];
__device__ __align__(128) unsigned g_ctr[16 * 32];
#define PROF_MARK(i) do {} while (0)

constexpr int A_STAGE = 16384, W_STAGE = 28672;
constexpr int OFF_A = 0;
constexpr int OFF_W = 3 * A_STAGE;
constexpr int OFF_S = OFF_W + 3 * W_STAGE;
constexpr int S_BLK = 21504;
constexpr int OFF_M = OFF_S + 4 * S_BLK;
constexpr int M_BAR = OFF_M, M_REL = OFF_M + 128, M_EPOCH = OFF_M + 192, M_CH = OFF_M + 208;
constexpr int M_COL = OFF_M + 256, M_ROW = OFF_M + 2048;
constexpr int SMEM_BYTES = OFF_M + 4096 + 1024;
constexpr int STG_BYTES = 7168;
constexpr int B_KFULL = 10240, B_TAB = 17152;
constexpr int PP = 544, P5 = 400, P7 = 272;
constexpr int B_P = 0, B_V3 = 12 * PP, B_V5 = B_V3 + 8 * PP, B_V7 = B_V5 + 8 * P5;
constexpr int T_A0 = 0, T_A1 = 96, T_A3 = 192, T_A2 = 288, T_A4 = 448, T_B5 = 544, T_B3 = 640, T_B7 = 736, T_BT = 896;

constexpr int BAR_S = 1, BAR_K = 2  , BAR_STAT = 6, BAR_G1 = 7, BAR_CONV = 8, BAR_FIN = 9, BAR_PP = 10  , BAR_C = 12;

__device__ __forceinline__ uint32_t smem_u32(const void* p) { return (uint32_t)__cvta_generic_to_shared(p); }
__device__ __forceinline__ void bar_sync(int id, int n) { asm volatile("bar.sync %0, %1;" ::"r"(id), "r"(n) : "memory"); }
__device__ __forceinline__ void bar_arrive(int id, int n) { asm volatile("bar.arrive %0, %1;" ::"r"(id), "r"(n) : "memory"); }
__device__ __forceinline__ void mbar_init(uint32_t bar, int cnt) { asm volatile("mbarrier.init.shared::cta.b64 [%0], %1;" ::"r"(bar), "r"(cnt) : "memory"); }
__device__ __forceinline__ void mbar_expect(uint32_t bar, int bytes) { asm volatile("mbarrier.arrive.expect_tx.shared::cta.b64 _, [%0], %1;" ::"r"(bar), "r"(bytes) : "memory"); }
__device__ __forceinline__ void mbar_wait(uint32_t bar, int parity) {
  for (int n = 0;; n++) {
    uint32_t ok;
    asm volatile("{ .reg .pred p; mbarrier.try_wait.parity.shared::cta.b64 p, [%1], %2; selp.u32 %0, 1, 0, p; }" : "=r"(ok) : "r"(bar), "r"(parity) : "memory");
    if (ok) break;
    if (n > (1 << 20)) __trap();
  }
}
__device__ __forceinline__ void tma2d(uint32_t dst, const CUtensorMap* m, int c0, int c1, uint32_t bar) {
  asm volatile("cp.async.bulk.tensor.2d.shared::cluster.global.mbarrier::complete_tx::bytes [%0], [%1, {%3, %4}], [%2];"
               ::"r"(dst), "l"(m), "r"(bar), "r"(c0), "r"(c1) : "memory");
}
__device__ __forceinline__ void tma3d(uint32_t dst, const CUtensorMap* m, int c0, int c1, int c2, uint32_t bar) {
  asm volatile("cp.async.bulk.tensor.3d.shared::cluster.global.mbarrier::complete_tx::bytes [%0], [%1, {%3, %4, %5}], [%2];"
               ::"r"(dst), "l"(m), "r"(bar), "r"(c0), "r"(c1), "r"(c2) : "memory");
}
__device__ __forceinline__ uint64_t mkdesc(uint32_t addr, uint32_t lbo, uint32_t sbo, int swz) {
  return (uint64_t)((addr & 0x3FFFF) >> 4) | ((uint64_t)(lbo >> 4) << 16) | ((uint64_t)(sbo >> 4) << 32) | ((uint64_t)swz << 62);
}
__device__ __forceinline__ void wg_fence() { asm volatile("wgmma.fence.sync.aligned;" ::: "memory"); }
__device__ __forceinline__ void wg_commit() { asm volatile("wgmma.commit_group.sync.aligned;" ::: "memory"); }
__device__ __forceinline__ void wg_wait0() { asm volatile("wgmma.wait_group.sync.aligned 0;" ::: "memory"); }
__device__ __forceinline__ void hmma(float& c0, float& c1, float& c2, float& c3, uint32_t a0, uint32_t a1, uint32_t a2, uint32_t a3, uint32_t b0, uint32_t b1) {
  asm("mma.sync.aligned.m16n8k16.row.col.f32.f16.f16.f32 {%0,%1,%2,%3}, {%4,%5,%6,%7}, {%8,%9}, {%0,%1,%2,%3};"
      : "+f"(c0), "+f"(c1), "+f"(c2), "+f"(c3) : "r"(a0), "r"(a1), "r"(a2), "r"(a3), "r"(b0), "r"(b1));
}
__device__ __forceinline__ void ldsm4(uint32_t& r0, uint32_t& r1, uint32_t& r2, uint32_t& r3, uint32_t addr) {
  asm volatile("ldmatrix.sync.aligned.m8n8.x4.shared.b16 {%0,%1,%2,%3}, [%4];" : "=r"(r0), "=r"(r1), "=r"(r2), "=r"(r3) : "r"(addr));
}
__device__ __forceinline__ void ldsm4t(uint32_t& r0, uint32_t& r1, uint32_t& r2, uint32_t& r3, uint32_t addr) {
  asm volatile("ldmatrix.sync.aligned.m8n8.x4.trans.shared.b16 {%0,%1,%2,%3}, [%4];" : "=r"(r0), "=r"(r1), "=r"(r2), "=r"(r3) : "r"(addr));
}
__device__ __forceinline__ void sts128(uint32_t addr, uint32_t a, uint32_t b, uint32_t c, uint32_t d) {
  asm volatile("st.shared.v4.b32 [%0], {%1,%2,%3,%4};" ::"r"(addr), "r"(a), "r"(b), "r"(c), "r"(d) : "memory");
}
__device__ __forceinline__ uint32_t lds32(uint32_t addr) { uint32_t v; asm volatile("ld.shared.b32 %0, [%1];" : "=r"(v) : "r"(addr)); return v; }
__device__ __forceinline__ void lds64(uint32_t& a, uint32_t& b, uint32_t addr) { asm volatile("ld.shared.v2.b32 {%0,%1}, [%2];" : "=r"(a), "=r"(b) : "r"(addr)); }
__device__ __forceinline__ uint32_t pack_h2(float lo, float hi) { uint32_t r; asm("cvt.rn.f16x2.f32 %0, %1, %2;" : "=r"(r) : "f"(hi), "f"(lo)); return r; }
__device__ __forceinline__ uint32_t pack_bf2(float lo, float hi) { uint32_t r; asm("cvt.rn.bf16x2.f32 %0, %1, %2;" : "=r"(r) : "f"(hi), "f"(lo)); return r; }
__device__ __forceinline__ float bf_lo(uint32_t v) { return __uint_as_float(v << 16); }
__device__ __forceinline__ float bf_hi(uint32_t v) { return __uint_as_float(v & 0xffff0000u); }
__device__ __forceinline__ float bf_round(float x) { return __bfloat162float(__float2bfloat16_rn(x)); }
__device__ __forceinline__ uint32_t hadd2(uint32_t a, uint32_t b) { uint32_t r; asm("add.rn.f16x2 %0, %1, %2;" : "=r"(r) : "r"(a), "r"(b)); return r; }
__device__ __forceinline__ uint32_t hmul2(uint32_t a, uint32_t b) { uint32_t r; asm("mul.rn.f16x2 %0, %1, %2;" : "=r"(r) : "r"(a), "r"(b)); return r; }
__device__ __forceinline__ uint32_t hfma2(uint32_t a, uint32_t b, uint32_t c) { uint32_t r; asm("fma.rn.f16x2 %0, %1, %2, %3;" : "=r"(r) : "r"(a), "r"(b), "r"(c)); return r; }
__device__ __forceinline__ uint32_t bsub2(uint32_t a, uint32_t b) { uint32_t r; asm("sub.rn.bf16x2 %0, %1, %2;" : "=r"(r) : "r"(a), "r"(b)); return r; }
__device__ __forceinline__ uint32_t badd2(uint32_t a, uint32_t b) { uint32_t r; asm("add.rn.bf16x2 %0, %1, %2;" : "=r"(r) : "r"(a), "r"(b)); return r; }
__device__ __forceinline__ uint32_t bmul2(uint32_t a, uint32_t b) { uint32_t r; asm("mul.rn.bf16x2 %0, %1, %2;" : "=r"(r) : "r"(a), "r"(b)); return r; }
__device__ __forceinline__ float ex2f(float x) { float r; asm("ex2.approx.ftz.f32 %0, %1;" : "=f"(r) : "f"(x)); return r; }
__device__ __forceinline__ float tanhf_fast(float x) { float r; asm("tanh.approx.f32 %0, %1;" : "=f"(r) : "f"(x)); return r; }
__device__ __forceinline__ void red_release(unsigned* p) { asm volatile("red.release.gpu.global.add.u32 [%0], 1;" ::"l"(p) : "memory"); }
__device__ __forceinline__ void wait_counter(const unsigned* p, unsigned target) {
  for (int n = 0;; n++) {
    unsigned v;
    asm volatile("ld.acquire.gpu.global.u32 %0, [%1];" : "=r"(v) : "l"(p) : "memory");
    if ((int)(v - target) >= 0) break;
    if (n > (1 << 20)) __trap();
  }
}
__device__ __forceinline__ void st_b128(uint4* p, uint32_t a, uint32_t b, uint32_t c, uint32_t d) {
  asm volatile("{ .reg .b64 lo, hi; .reg .b128 v; mov.b64 lo, {%1,%2}; mov.b64 hi, {%3,%4}; mov.b128 v, {lo, hi}; st.relaxed.gpu.global.b128 [%0], v; }"
               ::"l"(p), "r"(a), "r"(b), "r"(c), "r"(d) : "memory");
}
__device__ __forceinline__ void ld_b128(uint32_t (&r)[4], const uint4* p) {
  asm volatile("{ .reg .b64 lo, hi; .reg .b128 v; ld.relaxed.gpu.global.b128 v, [%4]; mov.b128 {lo, hi}, v; mov.b64 {%0,%1}, lo; mov.b64 {%2,%3}, hi; }"
               : "=r"(r[0]), "=r"(r[1]), "=r"(r[2]), "=r"(r[3]) : "l"(p) : "memory");
}
struct cf { float r, i; };
__device__ __forceinline__ cf cmul(cf a, cf b) { return {fmaf(a.r, b.r, -(a.i * b.i)), fmaf(a.r, b.i, a.i * b.r)}; }
__device__ __forceinline__ cf csq(cf a) { return {fmaf(a.r, a.r, -(a.i * a.i)), (a.r + a.r) * a.i}; }
__device__ __forceinline__ cf cexp_p(float zr2, float zi, float p) {
  float m = ex2f(zr2 * p), a = zi * p;
  return {m * __cosf(a), m * __sinf(a)};
}

__device__ __forceinline__ void wgmma_ss_n224(float (&d)[112], uint64_t da, uint64_t db, int scale_d) {
  asm volatile("{ .reg .pred p; setp.ne.b32 p, %114, 0;\n"
    "wgmma.mma_async.sync.aligned.m64n224k16.f32.bf16.bf16 {%0,%1,%2,%3,%4,%5,%6,%7,%8,%9,%10,%11,%12,%13,%14,%15,%16,%17,%18,%19,%20,%21,%22,%23,%24,%25,%26,%27,%28,%29,%30,%31,%32,%33,%34,%35,%36,%37,%38,%39,%40,%41,%42,%43,%44,%45,%46,%47,%48,%49,%50,%51,%52,%53,%54,%55,%56,%57,%58,%59,%60,%61,%62,%63,%64,%65,%66,%67,%68,%69,%70,%71,%72,%73,%74,%75,%76,%77,%78,%79,%80,%81,%82,%83,%84,%85,%86,%87,%88,%89,%90,%91,%92,%93,%94,%95,%96,%97,%98,%99,%100,%101,%102,%103,%104,%105,%106,%107,%108,%109,%110,%111}, %112, %113, p, 1, 1, 0, 1; }"
    : "+f"(d[0]), "+f"(d[1]), "+f"(d[2]), "+f"(d[3]), "+f"(d[4]), "+f"(d[5]), "+f"(d[6]), "+f"(d[7]),
      "+f"(d[8]), "+f"(d[9]), "+f"(d[10]), "+f"(d[11]), "+f"(d[12]), "+f"(d[13]), "+f"(d[14]), "+f"(d[15]),
      "+f"(d[16]), "+f"(d[17]), "+f"(d[18]), "+f"(d[19]), "+f"(d[20]), "+f"(d[21]), "+f"(d[22]), "+f"(d[23]),
      "+f"(d[24]), "+f"(d[25]), "+f"(d[26]), "+f"(d[27]), "+f"(d[28]), "+f"(d[29]), "+f"(d[30]), "+f"(d[31]),
      "+f"(d[32]), "+f"(d[33]), "+f"(d[34]), "+f"(d[35]), "+f"(d[36]), "+f"(d[37]), "+f"(d[38]), "+f"(d[39]),
      "+f"(d[40]), "+f"(d[41]), "+f"(d[42]), "+f"(d[43]), "+f"(d[44]), "+f"(d[45]), "+f"(d[46]), "+f"(d[47]),
      "+f"(d[48]), "+f"(d[49]), "+f"(d[50]), "+f"(d[51]), "+f"(d[52]), "+f"(d[53]), "+f"(d[54]), "+f"(d[55]),
      "+f"(d[56]), "+f"(d[57]), "+f"(d[58]), "+f"(d[59]), "+f"(d[60]), "+f"(d[61]), "+f"(d[62]), "+f"(d[63]),
      "+f"(d[64]), "+f"(d[65]), "+f"(d[66]), "+f"(d[67]), "+f"(d[68]), "+f"(d[69]), "+f"(d[70]), "+f"(d[71]),
      "+f"(d[72]), "+f"(d[73]), "+f"(d[74]), "+f"(d[75]), "+f"(d[76]), "+f"(d[77]), "+f"(d[78]), "+f"(d[79]),
      "+f"(d[80]), "+f"(d[81]), "+f"(d[82]), "+f"(d[83]), "+f"(d[84]), "+f"(d[85]), "+f"(d[86]), "+f"(d[87]),
      "+f"(d[88]), "+f"(d[89]), "+f"(d[90]), "+f"(d[91]), "+f"(d[92]), "+f"(d[93]), "+f"(d[94]), "+f"(d[95]),
      "+f"(d[96]), "+f"(d[97]), "+f"(d[98]), "+f"(d[99]), "+f"(d[100]), "+f"(d[101]), "+f"(d[102]), "+f"(d[103]),
      "+f"(d[104]), "+f"(d[105]), "+f"(d[106]), "+f"(d[107]), "+f"(d[108]), "+f"(d[109]), "+f"(d[110]), "+f"(d[111])
    : "l"(da), "l"(db), "r"(scale_d));
}

__device__ __forceinline__ void wgmma_rs_n56(float (&d)[28], uint32_t a0, uint32_t a1, uint32_t a2, uint32_t a3, uint64_t db, int scale_d) {
  asm volatile("{ .reg .pred p; setp.ne.b32 p, %33, 0;\n"
    "wgmma.mma_async.sync.aligned.m64n56k16.f32.bf16.bf16 {%0,%1,%2,%3,%4,%5,%6,%7,%8,%9,%10,%11,%12,%13,%14,%15,%16,%17,%18,%19,%20,%21,%22,%23,%24,%25,%26,%27}, {%28,%29,%30,%31}, %32, p, 1, 1, 1; }"
    : "+f"(d[0]), "+f"(d[1]), "+f"(d[2]), "+f"(d[3]), "+f"(d[4]), "+f"(d[5]), "+f"(d[6]), "+f"(d[7]),
      "+f"(d[8]), "+f"(d[9]), "+f"(d[10]), "+f"(d[11]), "+f"(d[12]), "+f"(d[13]), "+f"(d[14]), "+f"(d[15]),
      "+f"(d[16]), "+f"(d[17]), "+f"(d[18]), "+f"(d[19]), "+f"(d[20]), "+f"(d[21]), "+f"(d[22]), "+f"(d[23]),
      "+f"(d[24]), "+f"(d[25]), "+f"(d[26]), "+f"(d[27])
    : "r"(a0), "r"(a1), "r"(a2), "r"(a3), "l"(db), "r"(scale_d));
}

struct Params {
  const __nv_bfloat16 *x, *logA, *Aim, *Cre, *Cim, *logdt, *Dskip, *w1, *b1, *b2;
  __nv_bfloat16* out;
};

__device__ __forceinline__ uint32_t w2_slot(uint32_t sb, int p) {
  int i = p & 3;
  return sb + (i == 3 ? OFF_A : OFF_W + (i == 2 ? 0 : (i + 1) * W_STAGE));
}
__device__ __forceinline__ void issue_tile(int T, uint32_t sb, int rb, int fs, const CUtensorMap* mx, const CUtensorMap* mw1, const CUtensorMap* mw2) {
  uint32_t bar = sb + M_BAR + T * 8;
  if (T < 7) {
    int s = T % 3;
    mbar_expect(bar, A_STAGE + W_STAGE);
    tma2d(sb + OFF_A + s * A_STAGE, mx, 64 * T, 128 * rb, bar);
    tma3d(sb + OFF_W + s * W_STAGE, mw1, 0, 64 * T, 7 * fs, bar);
  } else {
    int p = T - 7;
    mbar_expect(bar, W_STAGE);
    tma2d(w2_slot(sb, p), mw2, 56 * ((fs + 1 + p) & 7), 224 * fs, bar);
  }
}
__device__ __forceinline__ void release_tile(int T, uint32_t sb, int rb, int fs, int lane, const CUtensorMap* mx, const CUtensorMap* mw1, const CUtensorMap* mw2) {
  if (lane == 0) {
    uint32_t old;
    asm volatile("atom.acq_rel.cta.shared.add.u32 %0, [%1], 1;" : "=r"(old) : "r"(sb + M_REL + T * 4) : "memory");
    if (old == 7) {
      int n = T < 7 ? T + 3 : T + 4;
      if (n <= 14) issue_tile(n, sb, rb, fs, mx, mw1, mw2);
      if (T == 6) issue_tile(10, sb, rb, fs, mx, mw1, mw2);
    }
  }
  __syncwarp();
}

__device__ __forceinline__ void kgen_batch(float (&acc)[2][3][4], float la, float ai, float cr, float ci, float dt, uint32_t stg, int lane) {
  float ar = bf_round(__expf(la));
  float zr2 = -(ar * dt) * 1.4426950408889634f, zi = ai * dt;
  cf w1 = cexp_p(zr2, zi, 1.f), v1 = cexp_p(zr2, -zi, 8.f), w256 = cexp_p(zr2, zi, 256.f);
  uint32_t re = stg + lane * 112, im = re + 3584;
  {
    cf v2 = csq(v1), v3 = cmul(v2, v1), v4 = csq(v2), v5 = cmul(v4, v1), v6 = csq(v3), v7 = cmul(v4, v3);
    cf u1 = csq(v4), u2 = csq(u1), u3 = cmul(u2, u1);
    uint32_t jr[4] = {pack_h2(1.f, v1.r), pack_h2(v2.r, v3.r), pack_h2(v4.r, v5.r), pack_h2(v6.r, v7.r)};
    uint32_t ji[4] = {pack_h2(0.f, v1.i), pack_h2(v2.i, v3.i), pack_h2(v4.i, v5.i), pack_h2(v6.i, v7.i)};
    sts128(re, jr[0], jr[1], jr[2], jr[3]);
    sts128(im, ji[0], ji[1], ji[2], ji[3]);
    cf us[3] = {u1, u2, u3};
#pragma unroll
    for (int m = 0; m < 3; m++) {
      uint32_t wr = pack_h2(us[m].r, us[m].r), wi = pack_h2(us[m].i, us[m].i), wn = wi ^ 0x80008000u;
      uint32_t r[4], q[4];
#pragma unroll
      for (int k = 0; k < 4; k++) {
        r[k] = hfma2(jr[k], wr, hmul2(ji[k], wn));
        q[k] = hfma2(jr[k], wi, hmul2(ji[k], wr));
      }
      sts128(re + 16 * (m + 1), r[0], r[1], r[2], r[3]);
      sts128(im + 16 * (m + 1), q[0], q[1], q[2], q[3]);
    }
  }
  {
    cf c[8];
    c[0] = cmul({cr, ci}, w1);
#pragma unroll
    for (int k = 1; k < 8; k++) c[k] = cmul(c[k - 1], w1);
    sts128(re + 64, pack_h2(c[0].r, c[1].r), pack_h2(c[2].r, c[3].r), pack_h2(c[4].r, c[5].r), pack_h2(c[6].r, c[7].r));
    sts128(im + 64, pack_h2(c[0].i, c[1].i), pack_h2(c[2].i, c[3].i), pack_h2(c[4].i, c[5].i), pack_h2(c[6].i, c[7].i));
    cf a258 = cmul(c[1], w256), a260 = cmul(c[3], w256), a262 = cmul(c[5], w256), a264 = cmul(c[7], w256);
    cf a516 = cmul(a260, w256), a520 = cmul(a264, w256), a772 = cmul(a516, w256), a776 = cmul(a520, w256);
    sts128(re + 80, pack_h2(a258.r, a260.r), pack_h2(a262.r, a264.r), pack_h2(a516.r, a520.r), pack_h2(a772.r, a776.r));
    sts128(im + 80, pack_h2(a258.i, a260.i), pack_h2(a262.i, a264.i), pack_h2(a516.i, a520.i), pack_h2(a772.i, a776.i));
    cf b0 = cmul(a776, w256), b1 = cmul(b0, w256), b2 = cmul(b1, w256), b3 = cmul(b2, w256);
    sts128(re + 96, pack_h2(b0.r, b1.r), pack_h2(b2.r, b3.r), 0u, 0u);
    sts128(im + 96, pack_h2(b0.i, b1.i), pack_h2(b2.i, b3.i), 0u, 0u);
  }
  __syncwarp();
  int mi = lane >> 3, row = lane & 7;
  uint32_t aA = stg + row * 112 + (mi >> 1) * 3584 + (mi & 1) * 16;
  uint32_t aB = stg + row * 112 + (mi & 1) * 3584 + (mi >> 1) * 16 + 64;
  uint32_t aC = stg + (row + (mi >> 1) * 8) * 112 + (mi & 1) * 3584 + 96;
#pragma unroll
  for (int kp = 0; kp < 2; kp++) {
    uint32_t c0, c1, c2, c3;
    ldsm4t(c0, c1, c2, c3, aC + kp * 1792);
#pragma unroll
    for (int kk = 0; kk < 2; kk++) {
      int ks = kp * 2 + kk;
      uint32_t a[2][4], b[4];
      ldsm4t(a[0][0], a[0][1], a[0][2], a[0][3], aA + ks * 896);
      ldsm4t(a[1][0], a[1][1], a[1][2], a[1][3], aA + ks * 896 + 32);
      ldsm4t(b[0], b[1], b[2], b[3], aB + ks * 896);
#pragma unroll
      for (int mt = 0; mt < 2; mt++) {
        hmma(acc[mt][0][0], acc[mt][0][1], acc[mt][0][2], acc[mt][0][3], a[mt][0], a[mt][1], a[mt][2], a[mt][3], b[0], b[1]);
        hmma(acc[mt][1][0], acc[mt][1][1], acc[mt][1][2], acc[mt][1][3], a[mt][0], a[mt][1], a[mt][2], a[mt][3], b[2], b[3]);
        hmma(acc[mt][2][0], acc[mt][2][1], acc[mt][2][2], acc[mt][2][3], a[mt][0], a[mt][1], a[mt][2], a[mt][3], kk ? c2 : c0, kk ? c3 : c1);
      }
    }
  }
  __syncwarp();
}

template <int WORDS, int J0, int STEP, int JLO, int JHI, int MUL, int OFF, bool TIE>
__device__ __forceinline__ void build_tab(uint32_t* tab, const unsigned short* kf, int lane) {
#pragma unroll
  for (int r = 0; r < WORDS / 32; r++) {
    int j = J0 + 32 * r + lane, k = j - STEP;
    int ij = TIE ? 16 * ((j + 1) >> 1) : MUL * j + OFF, ik = TIE ? 16 * ((k + 1) >> 1) : MUL * k + OFF;
    uint32_t lo = 0, hi = 0;
    if ((J0 + 32 * r >= JLO || j >= JLO) && (J0 + 32 * r + 31 <= JHI || j <= JHI)) lo = kf[ij];
    if ((J0 + 32 * r - STEP >= JLO || k >= JLO) && (J0 + 32 * r + 31 - STEP <= JHI || k <= JHI)) hi = kf[ik];
    tab[32 * r + lane] = lo | (hi << 16);
  }
}

template <int D0, int ND>
__device__ __forceinline__ void conv_A(float (&acc)[16][4], uint32_t ta, uint32_t lb) {
  uint32_t a[ND][3];
#pragma unroll
  for (int d = 0; d < ND; d++) { lds64(a[d][0], a[d][1], ta + 64 * (D0 + d)); a[d][2] = lds32(ta + 64 * (D0 + d) - 4); }
  constexpr int NP = (32 - D0) / 2, H = (NP + 1) / 2;
#pragma unroll
  for (int pp = 0; pp < H; pp++) {
    uint32_t b[2][4];
#pragma unroll
    for (int u = 0; u < 2; u++) { int p = pp + u * H; if (p < NP) ldsm4(b[u][0], b[u][1], b[u][2], b[u][3], lb + (2 * p - 1) * 16); }
#pragma unroll
    for (int d = 0; d < ND; d++)
#pragma unroll
      for (int u = 0; u < 2; u++) {
        int p = pp + u * H, dl = D0 + d, odd = dl & 1;
        int s = odd ? 2 * p - 1 : 2 * p, al = (s + dl) / 2;
        if (p < NP && al <= 15)
          hmma(acc[al][0], acc[al][1], acc[al][2], acc[al][3], a[d][0], a[d][1], a[d][2], a[d][0], b[u][odd ? 0 : 2], b[u][odd ? 1 : 3]);
      }
  }
}
template <int D0, int ND>
__device__ __forceinline__ void conv_B(float (&acc)[16][4], uint32_t tb, uint32_t lb) {
  uint32_t f[2 * ND + 1];
#pragma unroll
  for (int m = 0; m < 2 * ND + 1; m++) f[m] = lds32(tb + 32 * (2 * D0 - 1 + m));
  constexpr int NP = (16 - D0) / 2;
#pragma unroll
  for (int p = 0; p < NP; p++) {
    uint32_t b[4];
    ldsm4(b[0], b[1], b[2], b[3], lb + p * 64);
#pragma unroll
    for (int u = 0; u < 2; u++)
#pragma unroll
      for (int d = 0; d < ND; d++) {
        int al = 2 * p + u + D0 + d;
        if (al <= 15)
          hmma(acc[al][0], acc[al][2], acc[al][1], acc[al][3], f[2 * d + 1], f[2 * d + 2], f[2 * d], f[2 * d + 1], b[2 * u], b[2 * u + 1]);
      }
  }
}

__global__ void __launch_bounds__(NTHR, 1)
fused_kernel(const __grid_constant__ CUtensorMap mx, const __grid_constant__ CUtensorMap mw1, const __grid_constant__ CUtensorMap mw2, const Params P) {
  extern __shared__ unsigned char smem_raw[];
  const uint32_t sb = (smem_u32(smem_raw) + 1023u) & ~1023u;
  unsigned char* sm = smem_raw + (sb - smem_u32(smem_raw));
  const int tid = threadIdx.x, lane = tid & 31;
  const int warp = __shfl_sync(0xffffffffu, tid >> 5, 0);
  const int cta = blockIdx.x, rb = cta >> 3, fs = cta & 7;
  const bool has_ch = cta < 112;
  const int g = lane >> 2, q = lane & 3;

  if (tid == 0) {
#pragma unroll
    for (int i = 0; i < 15; i++) { mbar_init(sb + M_BAR + i * 8, 1); ((uint32_t*)(sm + M_REL))[i] = 0; }
    asm volatile("fence.mbarrier_init.release.cluster;" ::: "memory");
    asm volatile("fence.proxy.async.shared::cta;" ::: "memory");
    issue_tile(0, sb, rb, fs, &mx, &mw1, &mw2);
    issue_tile(1, sb, rb, fs, &mx, &mw1, &mw2);
    issue_tile(2, sb, rb, fs, &mx, &mw1, &mw2);
    asm volatile("prefetch.tensormap [%0];" ::"l"(&mw2) : "memory");
  }

  if (warp < 8) {
    const int wg = warp >> 2;
    if (has_ch) {
      const int c = warp & 3, d = cta * 4 + c, n0 = d * NS + wg * 128 + lane * 4, n1 = n0 ^ 128;
      uint2 vla = __ldg((const uint2*)(P.logA + n0)), vai = __ldg((const uint2*)(P.Aim + n0));
      uint2 vcr = __ldg((const uint2*)(P.Cre + n0)), vci = __ldg((const uint2*)(P.Cim + n0));
      uint2 ocr = __ldg((const uint2*)(P.Cre + n1)), oci = __ldg((const uint2*)(P.Cim + n1));
      float dt = bf_round(__expf(__bfloat162float(P.logdt[d])));
      __syncthreads();
      uint32_t mx2 = __vmaxu2(__vmaxu2(__vmaxu2(vcr.x & 0x7fff7fffu, vcr.y & 0x7fff7fffu), __vmaxu2(vci.x & 0x7fff7fffu, vci.y & 0x7fff7fffu)),
                              __vmaxu2(__vmaxu2(ocr.x & 0x7fff7fffu, ocr.y & 0x7fff7fffu), __vmaxu2(oci.x & 0x7fff7fffu, oci.y & 0x7fff7fffu)));
      uint32_t mxv = __reduce_max_sync(0xffffffffu, max(mx2 & 0xffffu, mx2 >> 16));
      int e = min(max((int)(mxv >> 7), 6), 254);
      float scale = __uint_as_float((uint32_t)(259 - e) << 23);
      if (wg == 0) {
        float s = (bf_lo(vcr.x) + bf_hi(vcr.x)) + (bf_lo(vcr.y) + bf_hi(vcr.y)) + (bf_lo(ocr.x) + bf_hi(ocr.x)) + (bf_lo(ocr.y) + bf_hi(ocr.y));
#pragma unroll
        for (int o = 16; o; o >>= 1) s += __shfl_xor_sync(0xffffffffu, s, o);
        if (lane == 0) { float* ch = (float*)(sm + M_CH); ch[c] = 2.f * dt * __uint_as_float((uint32_t)(e - 5) << 23); ch[4 + c] = s * scale; }
      }
      PROF_MARK(0);
      float kacc[2][3][4];
#pragma unroll
      for (int i = 0; i < 24; i++) (&kacc[0][0][0])[i] = 0.f;
      uint32_t stg = sb + OFF_S + c * S_BLK + wg * STG_BYTES;
#pragma unroll 1
      for (int b = 0; b < 4; b++) {
        uint32_t sh = (b & 1) ? 0u : 16u;
        uint32_t wla = (b & 2) ? vla.y : vla.x, wai = (b & 2) ? vai.y : vai.x, wcr = (b & 2) ? vcr.y : vcr.x, wci = (b & 2) ? vci.y : vci.x;
        kgen_batch(kacc, bf_hi(wla << sh), bf_hi(wai << sh), bf_hi(wcr << sh) * scale, bf_hi(wci << sh) * scale, dt, stg, lane);
      }
#pragma unroll
      for (int i = 0; i < 6; i++) {
        float* a = &kacc[0][0][0] + 4 * i;
        sts128(stg + i * 512 + lane * 16, __float_as_uint(a[0]), __float_as_uint(a[1]), __float_as_uint(a[2]), __float_as_uint(a[3]));
      }
      bar_arrive(BAR_K + c, 96);
    } else {
      __syncthreads();
      const int col0 = (cta - 112) * 112;
      float* red = (float*)(sm + OFF_S);
      if (tid < 224) {
        int ck = tid % 14, rg = tid / 14;
        float s[8];
#pragma unroll
        for (int i = 0; i < 8; i++) s[i] = 0.f;
        const uint4* src = (const uint4*)(P.w1 + (size_t)rg * FF + col0 + ck * 8);
#pragma unroll 7
        for (int i = 0; i < 28; i++) {
          uint4 v = __ldg(src + (size_t)i * 16 * FF / 8);
          s[0] += bf_lo(v.x); s[1] += bf_hi(v.x); s[2] += bf_lo(v.y); s[3] += bf_hi(v.y);
          s[4] += bf_lo(v.z); s[5] += bf_hi(v.z); s[6] += bf_lo(v.w); s[7] += bf_hi(v.w);
        }
#pragma unroll
        for (int i = 0; i < 8; i++) red[rg * 112 + ck * 8 + i] = s[i];
      }
      bar_sync(BAR_C, 256);
      if (tid < 112) {
        float s = 0.f;
#pragma unroll
        for (int i = 0; i < 16; i++) s += red[i * 112 + tid];
        g_cs[col0 + tid] = s;
      }
      bar_sync(BAR_C, 256);
      if (tid == 0) red_release(&g_ctr[2 * 32]);
    }
    PROF_MARK(1);

    uint32_t h[56];
    {
      float acc[112];
#pragma unroll 1
      for (int kb = 0; kb < 7; kb++) {
        int s = kb % 3;
        mbar_wait(sb + M_BAR + kb * 8, 0);
        uint64_t da = mkdesc(sb + OFF_A + s * A_STAGE + wg * 8192, 16, 1024, 1);
        uint64_t db = mkdesc(sb + OFF_W + s * W_STAGE, 4096, 512, 2);
        wg_fence();
#pragma unroll
        for (int k = 0; k < 4; k++) wgmma_ss_n224(acc, da + k * 2, db + k * 64, (kb | k) != 0);
        wg_commit();
        wg_wait0();
        release_tile(kb, sb, rb, fs, lane, &mx, &mw1, &mw2);
      }
      bar_arrive(BAR_G1, 384);
      PROF_MARK(2);
      bar_sync(BAR_STAT, 384);
      const int row = wg * 64 + (warp & 3) * 16 + g;
      float4 st0 = ((const float4*)(sm + M_ROW))[row], st1 = ((const float4*)(sm + M_ROW))[row + 8];
      float r0 = st0.w, k0 = -st0.w * st0.z, r1 = st1.w, k1 = -st1.w * st1.z;
#pragma unroll
      for (int i = 0; i < 28; i++) {
        float4 cv = ((const float4*)(sm + M_COL))[4 * i + q];
        float v[4] = {fmaf(r0, acc[4 * i], fmaf(k0, cv.x, cv.y)), fmaf(r0, acc[4 * i + 1], fmaf(k0, cv.z, cv.w)),
                      fmaf(r1, acc[4 * i + 2], fmaf(k1, cv.x, cv.y)), fmaf(r1, acc[4 * i + 3], fmaf(k1, cv.z, cv.w))};
#pragma unroll
        for (int e = 0; e < 4; e++) {
          float u = v[e] * fmaf(v[e] * v[e], 0.035677408136300125f, 0.7978845608028654f);
          float hh = 0.5f * v[e];
          v[e] = fmaf(hh, tanhf_fast(u), hh);
        }
        h[2 * i] = pack_bf2(v[0], v[1]);
        h[2 * i + 1] = pack_bf2(v[2], v[3]);
      }
    }
    const uint32_t tag = (*(const volatile uint32_t*)(sm + M_EPOCH) + 1u) << 16;
    PROF_MARK(3);
    bar_sync(BAR_CONV, 384);
    PROF_MARK(4);

    float o[28];
    uint32_t sum[4][4], inb[4][4];
#pragma unroll
    for (int v = 0; v < 4; v++)
#pragma unroll
      for (int k = 0; k < 4; k++) sum[v][k] = 0u;
    const uint4* rbase = g_part + (size_t)((rb * 8 + fs) * 8) * 1024 + tid;
    uint4* wbase = g_part + (size_t)(rb * 64 + fs) * 1024 + tid;
    auto fetch = [&](int p) {
      const uint4* s = rbase + ((fs - 1 - p) & 7) * 1024;
#pragma unroll
      for (int v = 0; v < 4; v++) ld_b128(inb[v], s + v * 256);
    };
    auto consume = [&](int p) {
      const uint4* s = rbase + ((fs - 1 - p) & 7) * 1024;
#pragma unroll
      for (int v = 0; v < 4; v++) {
        for (int n = 0; (inb[v][3] & 0xffff0000u) != tag; n++) {
          if (n > (1 << 20)) __trap();
          ld_b128(inb[v], s + v * 256);
        }
#pragma unroll
        for (int k = 0; k < 4; k++) sum[v][k] = hadd2(sum[v][k], inb[v][k]);
      }
    };
    if (wg == 1) bar_arrive(BAR_PP, 256);
#pragma unroll 1
    for (int p = 0; p < 8; p++) {
      mbar_wait(sb + M_BAR + (7 + p) * 8, 0);
      uint64_t db = mkdesc(w2_slot(sb, p), 16, 1024, 1);
      bar_sync(BAR_PP + wg, 256);
      wg_fence();
#pragma unroll
      for (int k = 0; k < 14; k++) wgmma_rs_n56(o, h[4 * k], h[4 * k + 1], h[4 * k + 2], h[4 * k + 3], db + k * 128, k != 0);
      wg_commit();
      if (wg == 0 || p < 7) bar_arrive(BAR_PP + (wg ^ 1), 256);
      wg_wait0();
      if (p < 7) {
        release_tile(7 + p, sb, rb, fs, lane, &mx, &mw1, &mw2);
        uint4* dst = wbase + ((fs + 1 + p) & 7) * 8192;
#pragma unroll
        for (int v = 0; v < 4; v++)
          st_b128(dst + v * 256, pack_h2(o[7 * v], o[7 * v + 1]), pack_h2(o[7 * v + 2], o[7 * v + 3]), pack_h2(o[7 * v + 4], o[7 * v + 5]),
                  (pack_h2(o[7 * v + 6], 0.f) & 0xffffu) | tag);
      }
      if (p >= 2) consume(p - 2);
      if (p >= 1) fetch(p - 1);
    }
    PROF_MARK(5);
    consume(6);
    PROF_MARK(6);
    bar_sync(BAR_FIN, 384);
    {
      const int row = rb * 128 + wg * 64 + (warp & 3) * 16 + g;
      uint32_t* op = (uint32_t*)(P.out + (size_t)row * DM + fs * 56 + 2 * q);
      const uint32_t* b2p = (const uint32_t*)(P.b2 + fs * 56 + 2 * q);
#pragma unroll
      for (int v = 0; v < 4; v++)
#pragma unroll
        for (int k = 0; k < 7; k++) {
          __half2 hv = *reinterpret_cast<__half2*>(&sum[v][k >> 1]);
          o[7 * v + k] += (k & 1) ? __high2float(hv) : __low2float(hv);
        }
#pragma unroll
      for (int i = 0; i < 7; i++) {
        uint4 xs = ((const uint4*)(sm + OFF_S))[i * 256 + tid];
        uint32_t bb = __ldg(b2p + 4 * i);
        float r[4];
#pragma unroll
        for (int e = 0; e < 4; e++) {
          float ho = 0.5f * (o[4 * i + e] + ((e & 1) ? bf_hi(bb) : bf_lo(bb)));
          float gt = fmaf(ho, tanhf_fast(ho), ho);
          uint32_t xw = (e & 2) ? xs.z : xs.x, sw = (e & 2) ? xs.w : xs.y;
          r[e] = (e & 1) ? fmaf(bf_hi(sw), gt, bf_hi(xw)) : fmaf(bf_lo(sw), gt, bf_lo(xw));
        }
        op[4 * i] = pack_bf2(r[0], r[1]);
        op[4 * i + 8 * DM / 2] = pack_bf2(r[2], r[3]);
      }
    }
    PROF_MARK(7);
  } else {
    const int v = warp - 8, st = tid - 256;
    unsigned epoch = 0;
    if (st == 0) epoch = atomicAdd(&g_ctr[0], 1u) >> 7;
    {
      const int i = 4 * v + (lane >> 3), j = lane & 7, t = rb * 128 + 8 * i + fs;
      uint32_t xv[28];
      const uint4* src = (const uint4*)(P.x + (size_t)t * DM) + j;
#pragma unroll
      for (int k = 0; k < 7; k++) { uint4 u = __ldg(src + 8 * k); xv[4 * k] = u.x; xv[4 * k + 1] = u.y; xv[4 * k + 2] = u.z; xv[4 * k + 3] = u.w; }
      __syncthreads();
      float s0 = 0.f, s1 = 0.f;
#pragma unroll
      for (int k = 0; k < 28; k++) { s0 += bf_lo(xv[k]); s1 += bf_hi(xv[k]); }
      s0 += s1;
#pragma unroll
      for (int o = 1; o < 8; o <<= 1) s0 += __shfl_xor_sync(0xffffffffu, s0, o);
      float mu = s0 * (1.f / DM);
      float q0 = 0.f, q1 = 0.f;
#pragma unroll
      for (int k = 0; k < 28; k++) { float a = bf_lo(xv[k]) - mu, b = bf_hi(xv[k]) - mu; q0 = fmaf(a, a, q0); q1 = fmaf(b, b, q1); }
      q0 += q1;
#pragma unroll
      for (int o = 1; o < 8; o <<= 1) q0 += __shfl_xor_sync(0xffffffffu, q0, o);
      float m1 = bf_round(mu);
      float d1 = bf_round(sqrtf(bf_round(bf_round(q0 * (1.f / DM)) + 1e-5f)));
      float i1 = 1.f / d1;
      uint32_t m2 = pack_bf2(m1, m1);
      s0 = 0.f; s1 = 0.f; q0 = 0.f; q1 = 0.f;
      uint32_t tb = sb + OFF_S + v * S_BLK + 2 * STG_BYTES + (i & 3) * 1024 + (2 * v + (i & 1)) * 16 + j * 16;
#pragma unroll
      for (int k = 0; k < 7; k++) {
        uint32_t hv[4];
#pragma unroll
        for (int e = 0; e < 4; e++) {
          uint32_t dd = bsub2(xv[4 * k + e], m2);
          uint32_t xn = pack_bf2(bf_lo(dd) * i1, bf_hi(dd) * i1);
          float a = bf_lo(xn), b = bf_hi(xn);
          s0 += a; s1 += b; q0 = fmaf(a, a, q0); q1 = fmaf(b, b, q1);
          hv[e] = pack_h2(a, b);
        }
        sts128(tb + k * 128, hv[0], hv[1], hv[2], hv[3]);
      }
      s0 += s1; q0 += q1;
#pragma unroll
      for (int o = 1; o < 8; o <<= 1) { s0 += __shfl_xor_sync(0xffffffffu, s0, o); q0 += __shfl_xor_sync(0xffffffffu, q0, o); }
      float mu2 = s0 * (1.f / DM);
      float var2 = fmaxf(fmaf(-mu2, mu2, q0 * (1.f / DM)), 0.f);
      float d2 = bf_round(sqrtf(bf_round(bf_round(var2) + 1e-5f)));
      if (j == 0) g_stats[t] = make_float4(m1, i1, fmaf(bf_round(mu2), d1, m1), 1.f / (d1 * d2));
      if (st == 0) *(volatile uint32_t*)(sm + M_EPOCH) = epoch;
      bar_sync(BAR_S, 128);
      epoch = *(const volatile uint32_t*)(sm + M_EPOCH);
      const int mi = lane >> 3, r = lane & 7, ri = 4 * (r >> 1) + 2 * (mi & 1) + (r & 1);
      uint32_t la = sb + OFF_S + (ri >> 2) * S_BLK + 2 * STG_BYTES + (ri & 3) * 1024 + r * 16 + (14 * v + (mi >> 1)) * 16;
      __half* dst = g_xnT + (size_t)(112 * v + g) * SEQ + fs * 256 + 16 * rb + 4 * q;
#pragma unroll
      for (int k = 0; k < 7; k++) {
        uint32_t r0, r1, r2, r3;
        ldsm4t(r0, r1, r2, r3, la + k * 32);
        *(uint2*)(dst + (size_t)(16 * k) * SEQ) = make_uint2(r0, r1);
        *(uint2*)(dst + (size_t)(16 * k + 8) * SEQ) = make_uint2(r2, r3);
      }
      bar_sync(BAR_S, 128);
      if (st == 0) red_release(&g_ctr[1 * 32]);
    }
    PROF_MARK(0);
    const int d = cta * 4 + v;
    unsigned char* blk = sm + OFF_S + v * S_BLK;
    const uint32_t bs = sb + OFF_S + v * S_BLK;
    float post = 0.f;
    uint32_t kdiag = 0;
    if (has_ch) {
      bar_sync(BAR_K + v, 96);
      PROF_MARK(1);
      unsigned short* kf = (unsigned short*)(blk + B_KFULL);
      post = ((const float*)(sm + M_CH))[v];
      const int pi[3] = {2 * q + 1, q < 2 ? 258 + 4 * q : 4 + 256 * q, 1032 + 512 * q};
      const int ps[3] = {1, q < 2 ? 2 : 4, 256};
#pragma unroll
      for (int i = 0; i < 6; i++) {
        float4 a = ((const float4*)blk)[i * 32 + lane], b = ((const float4*)(blk + STG_BYTES))[i * 32 + lane];
        uint32_t lo = pack_h2(a.x + b.x, a.y + b.y), hi = pack_h2(a.z + b.z, a.w + b.w);
        int mt = i / 3, nt = i % 3, p0 = 8 * (16 * mt + g) + pi[nt];
        if (nt < 2 || q < 2) {
          kf[p0] = (unsigned short)lo; kf[p0 + ps[nt]] = (unsigned short)(lo >> 16);
          kf[p0 + 64] = (unsigned short)hi; kf[p0 + 64 + ps[nt]] = (unsigned short)(hi >> 16);
        }
      }
      __syncwarp();
      if (lane == 0) { kf[0] = (unsigned short)pack_h2(((const float*)(sm + M_CH))[4 + v], 0.f); kf[257] = kf[256]; kf[514] = kf[512]; }
      kdiag = kf[1024];
      __syncwarp();
      uint32_t* tab = (uint32_t*)(blk + B_TAB);
      build_tab<96, -14, 2, 0, 64, 4, 0, false>(tab + T_A0, kf, lane);
      build_tab<96, -14, 2, 0, 64, 4, 1, false>(tab + T_A1, kf, lane);
      build_tab<96, -14, 2, 0, 63, 4, 3, false>(tab + T_A3, kf, lane);
      build_tab<160, -14, 2, 0, 128, 4, 2, false>(tab + T_A2, kf, lane);
      build_tab<96, 50, 2, 64, 127, 4, 4, false>(tab + T_A4, kf, lane);
      build_tab<96, 50, 1, 64, 127, 8, 8, false>(tab + T_B5, kf, lane);
      build_tab<96, 50, 1, 64, 127, 8, 4, false>(tab + T_B3, kf, lane);
      build_tab<160, 114, 1, 128, 255, 8, 8, false>(tab + T_B7, kf, lane);
      build_tab<160, 114, 1, 128, 255, 8, 4, true>(tab + T_BT, kf, lane);
      __syncwarp();
    }
    PROF_MARK(2);
    if (lane == 0) { wait_counter(&g_ctr[1 * 32], (epoch + 1) * 128u); }
    __syncwarp();
    PROF_MARK(3);
    uint32_t R[8][4];
    if (has_ch) {
      const uint4* src = (const uint4*)(g_xnT + (size_t)d * SEQ) + lane;
#pragma unroll
      for (int f = 0; f < 8; f++) { uint4 u = __ldcg(src + f * 32); R[f][0] = u.x; R[f][1] = u.y; R[f][2] = u.z; R[f][3] = u.w; }
    }
    ((float4*)(sm + M_ROW))[st] = __ldcg(&g_stats[rb * 128 + st]);
    if (lane == 0) wait_counter(&g_ctr[2 * 32], (epoch + 1) * 16u);
    __syncwarp();
    if (st < 112) {
      float2 cs = __ldcg((const float2*)(g_cs + fs * 224) + st);
      uint32_t bb = __ldg((const uint32_t*)(P.b1 + fs * 224) + st);
      ((float4*)(sm + M_COL))[st] = make_float4(cs.x, bf_lo(bb), cs.y, bf_hi(bb));
    }
    bar_arrive(BAR_STAT, 384);
    if (has_ch) {
      uint32_t Q[19][4];
#pragma unroll
      for (int f = 0; f < 8; f++) {
        uint32_t pv = __shfl_up_sync(0xffffffffu, R[f][3], 1);
        if (lane == 0) pv = 0;
#pragma unroll
        for (int k = 0; k < 4; k++) {
          Q[11 + f][k] = R[f][k];
          Q[3 + f][k] = __byte_perm(k ? R[f][k - 1] : pv, R[f][k], 0x5432);
          if (f >= 5) Q[f - 5][k] = k ? R[f][k - 1] : pv;
        }
      }
      uint32_t pa = bs + 16 + lane * 16;
#pragma unroll
      for (int f = 0; f < 12; f++) sts128(pa + B_P + f * PP, Q[7 + f][0], Q[7 + f][1], Q[7 + f][2], Q[7 + f][3]);
      if (lane < 20) sts128(bs + lane * PP, 0u, 0u, 0u, 0u);
      uint32_t B2[14][4], T3[12][4], V5[9][4];
#pragma unroll
      for (int k = 0; k < 4; k++) {
#pragma unroll
        for (int f = 0; f < 14; f++) B2[f][k] = hadd2(Q[f][k], Q[f + 1][k]);
#pragma unroll
        for (int f = 0; f < 12; f++) T3[f][k] = hadd2(B2[f + 2][k], Q[f + 4][k]);
#pragma unroll
        for (int f = 0; f < 9; f++) V5[f][k] = hadd2(B2[f][k], T3[f][k]);
      }
#pragma unroll
      for (int f = 0; f < 8; f++) {
        sts128(pa + B_V3 + f * PP, T3[f + 4][0], T3[f + 4][1], T3[f + 4][2], T3[f + 4][3]);
        if (lane < 24) sts128(bs + B_V5 + f * P5 + lane * 16, V5[f + 1][0], V5[f + 1][1], V5[f + 1][2], V5[f + 1][3]);
        if (lane < 16) sts128(bs + B_V7 + f * P7 + lane * 16, hadd2(V5[f][0], B2[f + 5][0]), hadd2(V5[f][1], B2[f + 5][1]), hadd2(V5[f][2], B2[f + 5][2]), hadd2(V5[f][3], B2[f + 5][3]));
      }
      __syncwarp();
    }
    PROF_MARK(4);
    bar_sync(BAR_G1, 384);
    PROF_MARK(5);
    if (has_ch) {
      float acc[16][4];
#pragma unroll
      for (int i = 0; i < 16; i++) { acc[i][0] = 0.f; acc[i][1] = 0.f; acc[i][2] = 0.f; acc[i][3] = 0.f; }
      const int mi = lane >> 3, n = lane & 7;
      const uint32_t tA = bs + B_TAB + (14 + 2 * g - 4 * q) * 4, tB = bs + B_TAB + (g - 2 * q) * 4;
      const uint32_t lA = bs + ((n >> 1) + 4 * (mi & 1)) * PP + 16 + ((mi >> 1) + (n & 1)) * 16;
      const int r8 = 4 * (n & 1) + (n >> 1);
#pragma unroll 1
      for (int s = 0; s < 3; s++) conv_A<0, 5>(acc, tA + s * 96 * 4, lA + (s == 2 ? 1 : 4 - s) * PP);
      conv_A<0, 9>(acc, tA + T_A2 * 4, lA + 2 * PP);
      conv_A<4, 5>(acc, tA + (T_A4 - 64) * 4, lA + B_V3);
      {
        uint32_t a0 = g == 2 * q ? kdiag : (g == 2 * q + 1 ? kdiag << 16 : 0u);
        const uint32_t lX = lA + PP + (mi >> 1) * 16;
#pragma unroll
        for (int p = 0; p < 4; p++) {
          uint32_t b[4];
          ldsm4(b[0], b[1], b[2], b[3], lX + p * 64);
          hmma(acc[8 + 2 * p][0], acc[8 + 2 * p][1], acc[8 + 2 * p][2], acc[8 + 2 * p][3], a0, 0u, 0u, a0, b[0], b[1]);
          hmma(acc[9 + 2 * p][0], acc[9 + 2 * p][1], acc[9 + 2 * p][2], acc[9 + 2 * p][3], a0, 0u, 0u, a0, b[2], b[3]);
        }
      }
#pragma unroll 1
      for (int s = 0; s < 2; s++) conv_B<4, 5>(acc, tB + (T_B5 - 50 + s * 96) * 4, s ? bs + B_V3 + r8 * PP + 16 + mi * 16 : bs + B_V5 + r8 * P5 + mi * 16);
#pragma unroll 1
      for (int s = 0; s < 2; s++) conv_B<8, 8>(acc, tB + (T_B7 - 114 + s * 160) * 4, s ? bs + B_P + r8 * PP + 16 + mi * 16 : bs + B_V7 + r8 * P7 + mi * 16);
      uint2* yd = g_y + (size_t)d * 512 + lane;
#pragma unroll
      for (int i = 0; i < 16; i++) yd[i * 32] = make_uint2(pack_bf2(acc[i][0] * post, acc[i][1] * post), pack_bf2(acc[i][2] * post, acc[i][3] * post));
      bar_arrive(BAR_CONV, 384);
      PROF_MARK(6);
      __syncwarp();
      if (lane == 0) red_release(&g_ctr[(8 + cta / 14) * 32]);
    } else {
      bar_arrive(BAR_CONV, 384);
    }
    {
      const int row = v * 16 + g;
      const uint32_t* xp = (const uint32_t*)(P.x + (size_t)(rb * 128 + row) * DM + fs * 56 + 2 * q);
      const uint32_t* dp = (const uint32_t*)(P.Dskip + fs * 56 + 2 * q);
      uint32_t xw[7][4], tw[7][4];
      uint32_t m2[4]; float i1[4];
#pragma unroll
      for (int k = 0; k < 4; k++) { float4 s4 = ((const float4*)(sm + M_ROW))[row + (k & 1) * 8 + (k >> 1) * 64]; m2[k] = pack_bf2(s4.x, s4.x); i1[k] = s4.y; }
#pragma unroll
      for (int i = 0; i < 7; i++)
#pragma unroll
        for (int k = 0; k < 4; k++) xw[i][k] = __ldg(xp + 4 * i + ((k & 1) * 8 + (k >> 1) * 64) * (DM / 2));
#pragma unroll
      for (int i = 0; i < 7; i++) {
        uint32_t dk = __ldg(dp + 4 * i);
#pragma unroll
        for (int k = 0; k < 4; k++) {
          uint32_t dd = bsub2(xw[i][k], m2[k]);
          tw[i][k] = bmul2(pack_bf2(bf_lo(dd) * i1[k], bf_hi(dd) * i1[k]), dk);
        }
      }
      if (lane == 0) wait_counter(&g_ctr[(8 + fs) * 32], (epoch + 1) * 56u);
      bar_sync(BAR_S, 128);
      PROF_MARK(7);
      const uint32_t* yp = (const uint32_t*)(g_y + (size_t)(fs * 56 + 2 * q) * 512 + rb * 32 + 8 * v + (g & 3)) + (g >> 2);
#pragma unroll
      for (int i = 0; i < 7; i++) {
        uint32_t y00 = __ldcg(yp + (8 * i) * 1024), y01 = __ldcg(yp + (8 * i + 1) * 1024);
        uint32_t y10 = __ldcg(yp + (8 * i) * 1024 + 8), y11 = __ldcg(yp + (8 * i + 1) * 1024 + 8);
        uint32_t a = sb + OFF_S + (i * 256 + st) * 16;
        sts128(a, xw[i][0], badd2(__byte_perm(y00, y01, 0x5410), tw[i][0]), xw[i][1], badd2(__byte_perm(y10, y11, 0x5410), tw[i][1]));
        sts128(a + 2048, xw[i][2], badd2(__byte_perm(y00, y01, 0x7632), tw[i][2]), xw[i][3], badd2(__byte_perm(y10, y11, 0x7632), tw[i][3]));
      }
      bar_arrive(BAR_FIN, 384);
      PROF_MARK(8);
    }
  }
}

typedef CUresult (*EncodeFn)(CUtensorMap*, CUtensorMapDataType, cuuint32_t, void*, const cuuint64_t*, const cuuint64_t*, const cuuint32_t*,
                             const cuuint32_t*, CUtensorMapInterleave, CUtensorMapSwizzle, CUtensorMapL2promotion, CUtensorMapFloatOOBfill);

}

extern "C" void kernel_launch(void* const* d_in, const int* in_sizes, int n_in, void* d_out, int out_size) {
  (void)in_sizes; (void)n_in; (void)out_size;
  static EncodeFn enc = nullptr;
  if (!enc) {
    void* fn = nullptr;
    cudaDriverEntryPointQueryResult qr;
    cudaGetDriverEntryPoint("cuTensorMapEncodeTiled", &fn, cudaEnableDefault, &qr);
    enc = (EncodeFn)fn;
    cudaFuncSetAttribute(fused_kernel, cudaFuncAttributeMaxDynamicSharedMemorySize, SMEM_BYTES);
  }
  typedef const __nv_bfloat16* bp;
  Params P;
  P.x = (bp)d_in[0]; P.logA = (bp)d_in[1]; P.Aim = (bp)d_in[2]; P.Cre = (bp)d_in[3]; P.Cim = (bp)d_in[4];
  P.logdt = (bp)d_in[5]; P.Dskip = (bp)d_in[6]; P.w1 = (bp)d_in[8]; P.b1 = (bp)d_in[9]; P.b2 = (bp)d_in[11];
  P.out = (__nv_bfloat16*)d_out;
  CUtensorMap mx, mw1, mw2;
  {
    cuuint64_t dims[2] = {DM, SEQ}, str[1] = {DM * 2}; cuuint32_t box[2] = {64, 128}, es[2] = {1, 1};
    enc(&mx, CU_TENSOR_MAP_DATA_TYPE_BFLOAT16, 2, d_in[0], dims, str, box, es, CU_TENSOR_MAP_INTERLEAVE_NONE, CU_TENSOR_MAP_SWIZZLE_128B,
        CU_TENSOR_MAP_L2_PROMOTION_L2_128B, CU_TENSOR_MAP_FLOAT_OOB_FILL_NONE);
  }
  {
    cuuint64_t dims[3] = {32, DM, FF / 32}, str[2] = {FF * 2, 64}; cuuint32_t box[3] = {32, 64, 7}, es[3] = {1, 1, 1};
    enc(&mw1, CU_TENSOR_MAP_DATA_TYPE_BFLOAT16, 3, d_in[8], dims, str, box, es, CU_TENSOR_MAP_INTERLEAVE_NONE, CU_TENSOR_MAP_SWIZZLE_64B,
        CU_TENSOR_MAP_L2_PROMOTION_L2_128B, CU_TENSOR_MAP_FLOAT_OOB_FILL_NONE);
  }
  {
    cuuint64_t dims[2] = {DM, FF}, str[1] = {DM * 2}; cuuint32_t box[2] = {64, 224}, es[2] = {1, 1};
    enc(&mw2, CU_TENSOR_MAP_DATA_TYPE_BFLOAT16, 2, d_in[10], dims, str, box, es, CU_TENSOR_MAP_INTERLEAVE_NONE, CU_TENSOR_MAP_SWIZZLE_128B,
        CU_TENSOR_MAP_L2_PROMOTION_L2_128B, CU_TENSOR_MAP_FLOAT_OOB_FILL_NONE);
  }
  fused_kernel<<<NCTA, NTHR, SMEM_BYTES, cudaStreamPerThread>>>(mx, mw1, mw2, P);
}
```

```cpp
#include <cuda_runtime.h>
#include <cuda_bf16.h>
#include <cuda_fp16.h>
#include <cuda.h>
#include <stdint.h>

#define EXP 0
namespace {

constexpr int SEQ = 2048, DM = 448, FF = 1792, NS = 256;
constexpr int NCTA = 128, NTHR = 384;

__device__ __align__(128) __half g_xnT[DM * SEQ];
__device__ __align__(128) float4 g_stats[SEQ];
__device__ __align__(128) float g_cs[FF];
__device__ __align__(128) uint2 g_y[DM * 16 * 32];
__device__ __align__(128) uint4 g_part[16 * 8 * 8 * 4 * 256];
__device__ __align__(128) unsigned g_ctr[16 * 32];
#define PROF_MARK(i) do {} while (0)

constexpr int A_STAGE = 16384, W_STAGE = 28672;
constexpr int OFF_A = 0;
constexpr int OFF_W = 3 * A_STAGE;
constexpr int OFF_S = OFF_W + 3 * W_STAGE;
constexpr int S_BLK = 21504;
constexpr int OFF_M = OFF_S + 4 * S_BLK;
constexpr int M_BAR = OFF_M, M_REL = OFF_M + 128, M_EPOCH = OFF_M + 192, M_CH = OFF_M + 208;
constexpr int M_COL = OFF_M + 256, M_ROW = OFF_M + 2048;
constexpr int SMEM_BYTES = OFF_M + 4096 + 1024;
constexpr int STG_BYTES = 7168;
constexpr int B_KFULL = 10240, B_TAB = 17152;
constexpr int PP = 544, P5 = 400, P7 = 272;
constexpr int B_P = 0, B_V3 = 12 * PP, B_V5 = B_V3 + 8 * PP, B_V7 = B_V5 + 8 * P5;
constexpr int T_A0 = 0, T_A1 = 96, T_A3 = 192, T_A2 = 288, T_A4 = 448, T_B5 = 544, T_B3 = 640, T_B7 = 736, T_BT = 896;

constexpr int BAR_S = 1, BAR_K = 2  , BAR_STAT = 6, BAR_G1 = 7, BAR_CONV = 8, BAR_FIN = 9, BAR_PP = 10  , BAR_C = 12;

__device__ __forceinline__ uint32_t smem_u32(const void* p) { return (uint32_t)__cvta_generic_to_shared(p); }
__device__ __forceinline__ void bar_sync(int id, int n) { asm volatile("bar.sync %0, %1;" ::"r"(id), "r"(n) : "memory"); }
__device__ __forceinline__ void bar_arrive(int id, int n) { asm volatile("bar.arrive %0, %1;" ::"r"(id), "r"(n) : "memory"); }
__device__ __forceinline__ void mbar_init(uint32_t bar, int cnt) { asm volatile("mbarrier.init.shared::cta.b64 [%0], %1;" ::"r"(bar), "r"(cnt) : "memory"); }
__device__ __forceinline__ void mbar_expect(uint32_t bar, int bytes) { asm volatile("mbarrier.arrive.expect_tx.shared::cta.b64 _, [%0], %1;" ::"r"(bar), "r"(bytes) : "memory"); }
__device__ __forceinline__ void mbar_wait(uint32_t bar, int parity) {
  for (int n = 0;; n++) {
    uint32_t ok;
    asm volatile("{ .reg .pred p; mbarrier.try_wait.parity.shared::cta.b64 p, [%1], %2; selp.u32 %0, 1, 0, p; }" : "=r"(ok) : "r"(bar), "r"(parity) : "memory");
    if (ok) break;
    if (n > (1 << 20)) __trap();
  }
}
__device__ __forceinline__ void tma2d(uint32_t dst, const CUtensorMap* m, int c0, int c1, uint32_t bar) {
  asm volatile("cp.async.bulk.tensor.2d.shared::cluster.global.mbarrier::complete_tx::bytes [%0], [%1, {%3, %4}], [%2];"
               ::"r"(dst), "l"(m), "r"(bar), "r"(c0), "r"(c1) : "memory");
}
__device__ __forceinline__ void tma3d(uint32_t dst, const CUtensorMap* m, int c0, int c1, int c2, uint32_t bar) {
  asm volatile("cp.async.bulk.tensor.3d.shared::cluster.global.mbarrier::complete_tx::bytes [%0], [%1, {%3, %4, %5}], [%2];"
               ::"r"(dst), "l"(m), "r"(bar), "r"(c0), "r"(c1), "r"(c2) : "memory");
}
__device__ __forceinline__ uint64_t mkdesc(uint32_t addr, uint32_t lbo, uint32_t sbo, int swz) {
  return (uint64_t)((addr & 0x3FFFF) >> 4) | ((uint64_t)(lbo >> 4) << 16) | ((uint64_t)(sbo >> 4) << 32) | ((uint64_t)swz << 62);
}
__device__ __forceinline__ void wg_fence() { asm volatile("wgmma.fence.sync.aligned;" ::: "memory"); }
__device__ __forceinline__ void wg_commit() { asm volatile("wgmma.commit_group.sync.aligned;" ::: "memory"); }
__device__ __forceinline__ void wg_wait0() { asm volatile("wgmma.wait_group.sync.aligned 0;" ::: "memory"); }
__device__ __forceinline__ void hmma(float& c0, float& c1, float& c2, float& c3, uint32_t a0, uint32_t a1, uint32_t a2, uint32_t a3, uint32_t b0, uint32_t b1) {
  asm("mma.sync.aligned.m16n8k16.row.col.f32.f16.f16.f32 {%0,%1,%2,%3}, {%4,%5,%6,%7}, {%8,%9}, {%0,%1,%2,%3};"
      : "+f"(c0), "+f"(c1), "+f"(c2), "+f"(c3) : "r"(a0), "r"(a1), "r"(a2), "r"(a3), "r"(b0), "r"(b1));
}
__device__ __forceinline__ void ldsm4(uint32_t& r0, uint32_t& r1, uint32_t& r2, uint32_t& r3, uint32_t addr) {
  asm volatile("ldmatrix.sync.aligned.m8n8.x4.shared.b16 {%0,%1,%2,%3}, [%4];" : "=r"(r0), "=r"(r1), "=r"(r2), "=r"(r3) : "r"(addr));
}
__device__ __forceinline__ void ldsm4t(uint32_t& r0, uint32_t& r1, uint32_t& r2, uint32_t& r3, uint32_t addr) {
  asm volatile("ldmatrix.sync.aligned.m8n8.x4.trans.shared.b16 {%0,%1,%2,%3}, [%4];" : "=r"(r0), "=r"(r1), "=r"(r2), "=r"(r3) : "r"(addr));
}
__device__ __forceinline__ void sts128(uint32_t addr, uint32_t a, uint32_t b, uint32_t c, uint32_t d) {
  asm volatile("st.shared.v4.b32 [%0], {%1,%2,%3,%4};" ::"r"(addr), "r"(a), "r"(b), "r"(c), "r"(d) : "memory");
}
__device__ __forceinline__ uint32_t lds32(uint32_t addr) { uint32_t v; asm volatile("ld.volatile.shared.b32 %0, [%1];" : "=r"(v) : "r"(addr)); return v; }
__device__ __forceinline__ void lds64(uint32_t& a, uint32_t& b, uint32_t addr) { asm volatile("ld.shared.v2.b32 {%0,%1}, [%2];" : "=r"(a), "=r"(b) : "r"(addr)); }
__device__ __forceinline__ uint32_t pack_h2(float lo, float hi) { uint32_t r; asm("cvt.rn.f16x2.f32 %0, %1, %2;" : "=r"(r) : "f"(hi), "f"(lo)); return r; }
__device__ __forceinline__ uint32_t pack_bf2(float lo, float hi) { uint32_t r; asm("cvt.rn.bf16x2.f32 %0, %1, %2;" : "=r"(r) : "f"(hi), "f"(lo)); return r; }
__device__ __forceinline__ float bf_lo(uint32_t v) { return __uint_as_float(v << 16); }
__device__ __forceinline__ float bf_hi(uint32_t v) { return __uint_as_float(v & 0xffff0000u); }
__device__ __forceinline__ float bf_round(float x) { return __bfloat162float(__float2bfloat16_rn(x)); }
__device__ __forceinline__ uint32_t hadd2(uint32_t a, uint32_t b) { uint32_t r; asm("add.rn.f16x2 %0, %1, %2;" : "=r"(r) : "r"(a), "r"(b)); return r; }
__device__ __forceinline__ uint32_t hmul2(uint32_t a, uint32_t b) { uint32_t r; asm("mul.rn.f16x2 %0, %1, %2;" : "=r"(r) : "r"(a), "r"(b)); return r; }
__device__ __forceinline__ uint32_t hfma2(uint32_t a, uint32_t b, uint32_t c) { uint32_t r; asm("fma.rn.f16x2 %0, %1, %2, %3;" : "=r"(r) : "r"(a), "r"(b), "r"(c)); return r; }
__device__ __forceinline__ uint32_t bsub2(uint32_t a, uint32_t b) { uint32_t r; asm("sub.rn.bf16x2 %0, %1, %2;" : "=r"(r) : "r"(a), "r"(b)); return r; }
__device__ __forceinline__ uint32_t badd2(uint32_t a, uint32_t b) { uint32_t r; asm("add.rn.bf16x2 %0, %1, %2;" : "=r"(r) : "r"(a), "r"(b)); return r; }
__device__ __forceinline__ uint32_t bmul2(uint32_t a, uint32_t b) { uint32_t r; asm("mul.rn.bf16x2 %0, %1, %2;" : "=r"(r) : "r"(a), "r"(b)); return r; }
__device__ __forceinline__ float ex2f(float x) { float r; asm("ex2.approx.ftz.f32 %0, %1;" : "=f"(r) : "f"(x)); return r; }
__device__ __forceinline__ float tanhf_fast(float x) { float r; asm("tanh.approx.f32 %0, %1;" : "=f"(r) : "f"(x)); return r; }
__device__ __forceinline__ void red_release(unsigned* p) { asm volatile("red.release.gpu.global.add.u32 [%0], 1;" ::"l"(p) : "memory"); }
__device__ __forceinline__ void wait_counter(const unsigned* p, unsigned target) {
  for (int n = 0;; n++) {
    unsigned v;
    asm volatile("ld.acquire.gpu.global.u32 %0, [%1];" : "=r"(v) : "l"(p) : "memory");
    if ((int)(v - target) >= 0) break;
    if (n > (1 << 20)) __trap();
  }
}
__device__ __forceinline__ void st_b128(uint4* p, uint32_t a, uint32_t b, uint32_t c, uint32_t d) {
  asm volatile("{ .reg .b64 lo, hi; .reg .b128 v; mov.b64 lo, {%1,%2}; mov.b64 hi, {%3,%4}; mov.b128 v, {lo, hi}; st.relaxed.gpu.global.b128 [%0], v; }"
               ::"l"(p), "r"(a), "r"(b), "r"(c), "r"(d) : "memory");
}
__device__ __forceinline__ void ld_b128(uint32_t (&r)[4], const uint4* p) {
  asm volatile("{ .reg .b64 lo, hi; .reg .b128 v; ld.relaxed.gpu.global.b128 v, [%4]; mov.b128 {lo, hi}, v; mov.b64 {%0,%1}, lo; mov.b64 {%2,%3}, hi; }"
               : "=r"(r[0]), "=r"(r[1]), "=r"(r[2]), "=r"(r[3]) : "l"(p) : "memory");
}
struct cf { float r, i; };
__device__ __forceinline__ cf cmul(cf a, cf b) { return {fmaf(a.r, b.r, -(a.i * b.i)), fmaf(a.r, b.i, a.i * b.r)}; }
__device__ __forceinline__ cf csq(cf a) { return {fmaf(a.r, a.r, -(a.i * a.i)), (a.r + a.r) * a.i}; }
__device__ __forceinline__ cf cexp_p(float zr2, float zi, float p) {
  float m = ex2f(zr2 * p), a = zi * p;
  return {m * __cosf(a), m * __sinf(a)};
}

__device__ __forceinline__ void wgmma_ss_n224(float (&d)[112], uint64_t da, uint64_t db, int scale_d) {
  asm volatile("{ .reg .pred p; setp.ne.b32 p, %114, 0;\n"
    "wgmma.mma_async.sync.aligned.m64n224k16.f32.bf16.bf16 {%0,%1,%2,%3,%4,%5,%6,%7,%8,%9,%10,%11,%12,%13,%14,%15,%16,%17,%18,%19,%20,%21,%22,%23,%24,%25,%26,%27,%28,%29,%30,%31,%32,%33,%34,%35,%36,%37,%38,%39,%40,%41,%42,%43,%44,%45,%46,%47,%48,%49,%50,%51,%52,%53,%54,%55,%56,%57,%58,%59,%60,%61,%62,%63,%64,%65,%66,%67,%68,%69,%70,%71,%72,%73,%74,%75,%76,%77,%78,%79,%80,%81,%82,%83,%84,%85,%86,%87,%88,%89,%90,%91,%92,%93,%94,%95,%96,%97,%98,%99,%100,%101,%102,%103,%104,%105,%106,%107,%108,%109,%110,%111}, %112, %113, p, 1, 1, 0, 1; }"
    : "+f"(d[0]), "+f"(d[1]), "+f"(d[2]), "+f"(d[3]), "+f"(d[4]), "+f"(d[5]), "+f"(d[6]), "+f"(d[7]),
      "+f"(d[8]), "+f"(d[9]), "+f"(d[10]), "+f"(d[11]), "+f"(d[12]), "+f"(d[13]), "+f"(d[14]), "+f"(d[15]),
      "+f"(d[16]), "+f"(d[17]), "+f"(d[18]), "+f"(d[19]), "+f"(d[20]), "+f"(d[21]), "+f"(d[22]), "+f"(d[23]),
      "+f"(d[24]), "+f"(d[25]), "+f"(d[26]), "+f"(d[27]), "+f"(d[28]), "+f"(d[29]), "+f"(d[30]), "+f"(d[31]),
      "+f"(d[32]), "+f"(d[33]), "+f"(d[34]), "+f"(d[35]), "+f"(d[36]), "+f"(d[37]), "+f"(d[38]), "+f"(d[39]),
      "+f"(d[40]), "+f"(d[41]), "+f"(d[42]), "+f"(d[43]), "+f"(d[44]), "+f"(d[45]), "+f"(d[46]), "+f"(d[47]),
      "+f"(d[48]), "+f"(d[49]), "+f"(d[50]), "+f"(d[51]), "+f"(d[52]), "+f"(d[53]), "+f"(d[54]), "+f"(d[55]),
      "+f"(d[56]), "+f"(d[57]), "+f"(d[58]), "+f"(d[59]), "+f"(d[60]), "+f"(d[61]), "+f"(d[62]), "+f"(d[63]),
      "+f"(d[64]), "+f"(d[65]), "+f"(d[66]), "+f"(d[67]), "+f"(d[68]), "+f"(d[69]), "+f"(d[70]), "+f"(d[71]),
      "+f"(d[72]), "+f"(d[73]), "+f"(d[74]), "+f"(d[75]), "+f"(d[76]), "+f"(d[77]), "+f"(d[78]), "+f"(d[79]),
      "+f"(d[80]), "+f"(d[81]), "+f"(d[82]), "+f"(d[83]), "+f"(d[84]), "+f"(d[85]), "+f"(d[86]), "+f"(d[87]),
      "+f"(d[88]), "+f"(d[89]), "+f"(d[90]), "+f"(d[91]), "+f"(d[92]), "+f"(d[93]), "+f"(d[94]), "+f"(d[95]),
      "+f"(d[96]), "+f"(d[97]), "+f"(d[98]), "+f"(d[99]), "+f"(d[100]), "+f"(d[101]), "+f"(d[102]), "+f"(d[103]),
      "+f"(d[104]), "+f"(d[105]), "+f"(d[106]), "+f"(d[107]), "+f"(d[108]), "+f"(d[109]), "+f"(d[110]), "+f"(d[111])
    : "l"(da), "l"(db), "r"(scale_d));
}

__device__ __forceinline__ void wgmma_rs_n56(float (&d)[28], uint32_t a0, uint32_t a1, uint32_t a2, uint32_t a3, uint64_t db, int scale_d) {
  asm volatile("{ .reg .pred p; setp.ne.b32 p, %33, 0;\n"
    "wgmma.mma_async.sync.aligned.m64n56k16.f32.bf16.bf16 {%0,%1,%2,%3,%4,%5,%6,%7,%8,%9,%10,%11,%12,%13,%14,%15,%16,%17,%18,%19,%20,%21,%22,%23,%24,%25,%26,%27}, {%28,%29,%30,%31}, %32, p, 1, 1, 1; }"
    : "+f"(d[0]), "+f"(d[1]), "+f"(d[2]), "+f"(d[3]), "+f"(d[4]), "+f"(d[5]), "+f"(d[6]), "+f"(d[7]),
      "+f"(d[8]), "+f"(d[9]), "+f"(d[10]), "+f"(d[11]), "+f"(d[12]), "+f"(d[13]), "+f"(d[14]), "+f"(d[15]),
      "+f"(d[16]), "+f"(d[17]), "+f"(d[18]), "+f"(d[19]), "+f"(d[20]), "+f"(d[21]), "+f"(d[22]), "+f"(d[23]),
      "+f"(d[24]), "+f"(d[25]), "+f"(d[26]), "+f"(d[27])
    : "r"(a0), "r"(a1), "r"(a2), "r"(a3), "l"(db), "r"(scale_d));
}

struct Params {
  const __nv_bfloat16 *x, *logA, *Aim, *Cre, *Cim, *logdt, *Dskip, *w1, *b1, *b2;
  __nv_bfloat16* out;
};

__device__ __forceinline__ uint32_t w2_slot(uint32_t sb, int p) {
  int i = p & 3;
  return sb + (i == 3 ? OFF_A : OFF_W + (i == 2 ? 0 : (i + 1) * W_STAGE));
}
__device__ __forceinline__ void issue_tile(int T, uint32_t sb, int rb, int fs, const CUtensorMap* mx, const CUtensorMap* mw1, const CUtensorMap* mw2) {
  uint32_t bar = sb + M_BAR + T * 8;
  if (T < 7) {
    int s = T % 3;
    mbar_expect(bar, A_STAGE + W_STAGE);
    tma2d(sb + OFF_A + s * A_STAGE, mx, 64 * T, 128 * rb, bar);
    tma3d(sb + OFF_W + s * W_STAGE, mw1, 0, 64 * T, 7 * fs, bar);
  } else {
    int p = T - 7;
    mbar_expect(bar, W_STAGE);
    tma2d(w2_slot(sb, p), mw2, 56 * ((fs + 1 + p) & 7), 224 * fs, bar);
  }
}
__device__ __forceinline__ void release_tile(int T, uint32_t sb, int rb, int fs, int lane, const CUtensorMap* mx, const CUtensorMap* mw1, const CUtensorMap* mw2) {
  if (lane == 0) {
    uint32_t old;
    asm volatile("atom.relaxed.cta.shared.add.u32 %0, [%1], 1;" : "=r"(old) : "r"(sb + M_REL + T * 4) : "memory");
    if (old == 7) {
      int n = T < 7 ? T + 3 : T + 4;
      if (n <= 14) issue_tile(n, sb, rb, fs, mx, mw1, mw2);
      if (T == 6) issue_tile(10, sb, rb, fs, mx, mw1, mw2);
    }
  }
  __syncwarp();
}

__device__ __forceinline__ void kgen_batch(float (&acc)[2][3][4], float la, float ai, float cr, float ci, float dt, uint32_t stg, int lane) {
  float ar = bf_round(__expf(la));
  float zr2 = -(ar * dt) * 1.4426950408889634f, zi = ai * dt;
  cf w1 = cexp_p(zr2, zi, 1.f), v1 = cexp_p(zr2, -zi, 8.f), w256 = cexp_p(zr2, zi, 256.f);
  uint32_t re = stg + lane * 112, im = re + 3584;
  {
    cf v2 = csq(v1), v3 = cmul(v2, v1), v4 = csq(v2), v5 = cmul(v4, v1), v6 = csq(v3), v7 = cmul(v4, v3);
    cf u1 = csq(v4), u2 = csq(u1), u3 = cmul(u2, u1);
    uint32_t jr[4] = {pack_h2(1.f, v1.r), pack_h2(v2.r, v3.r), pack_h2(v4.r, v5.r), pack_h2(v6.r, v7.r)};
    uint32_t ji[4] = {pack_h2(0.f, v1.i), pack_h2(v2.i, v3.i), pack_h2(v4.i, v5.i), pack_h2(v6.i, v7.i)};
    sts128(re, jr[0], jr[1], jr[2], jr[3]);
    sts128(im, ji[0], ji[1], ji[2], ji[3]);
    cf us[3] = {u1, u2, u3};
#pragma unroll
    for (int m = 0; m < 3; m++) {
      uint32_t wr = pack_h2(us[m].r, us[m].r), wi = pack_h2(us[m].i, us[m].i), wn = wi ^ 0x80008000u;
      uint32_t r[4], q[4];
#pragma unroll
      for (int k = 0; k < 4; k++) {
        r[k] = hfma2(jr[k], wr, hmul2(ji[k], wn));
        q[k] = hfma2(jr[k], wi, hmul2(ji[k], wr));
      }
      sts128(re + 16 * (m + 1), r[0], r[1], r[2], r[3]);
      sts128(im + 16 * (m + 1), q[0], q[1], q[2], q[3]);
    }
  }
  {
    cf c[8];
    c[0] = cmul({cr, ci}, w1);
#pragma unroll
    for (int k = 1; k < 8; k++) c[k] = cmul(c[k - 1], w1);
    sts128(re + 64, pack_h2(c[0].r, c[1].r), pack_h2(c[2].r, c[3].r), pack_h2(c[4].r, c[5].r), pack_h2(c[6].r, c[7].r));
    sts128(im + 64, pack_h2(c[0].i, c[1].i), pack_h2(c[2].i, c[3].i), pack_h2(c[4].i, c[5].i), pack_h2(c[6].i, c[7].i));
    cf a258 = cmul(c[1], w256), a260 = cmul(c[3], w256), a262 = cmul(c[5], w256), a264 = cmul(c[7], w256);
    cf a516 = cmul(a260, w256), a520 = cmul(a264, w256), a772 = cmul(a516, w256), a776 = cmul(a520, w256);
    sts128(re + 80, pack_h2(a258.r, a260.r), pack_h2(a262.r, a264.r), pack_h2(a516.r, a520.r), pack_h2(a772.r, a776.r));
    sts128(im + 80, pack_h2(a258.i, a260.i), pack_h2(a262.i, a264.i), pack_h2(a516.i, a520.i), pack_h2(a772.i, a776.i));
    cf b0 = cmul(a776, w256), b1 = cmul(b0, w256), b2 = cmul(b1, w256), b3 = cmul(b2, w256);
    sts128(re + 96, pack_h2(b0.r, b1.r), pack_h2(b2.r, b3.r), 0u, 0u);
    sts128(im + 96, pack_h2(b0.i, b1.i), pack_h2(b2.i, b3.i), 0u, 0u);
  }
  __syncwarp();
  int mi = lane >> 3, row = lane & 7;
  uint32_t aA = stg + row * 112 + (mi >> 1) * 3584 + (mi & 1) * 16;
  uint32_t aB = stg + row * 112 + (mi & 1) * 3584 + (mi >> 1) * 16 + 64;
  uint32_t aC = stg + (row + (mi >> 1) * 8) * 112 + (mi & 1) * 3584 + 96;
#pragma unroll
  for (int kp = 0; kp < 2; kp++) {
    uint32_t c0, c1, c2, c3;
    ldsm4t(c0, c1, c2, c3, aC + kp * 1792);
#pragma unroll
    for (int kk = 0; kk < 2; kk++) {
      int ks = kp * 2 + kk;
      uint32_t a[2][4], b[4];
      ldsm4t(a[0][0], a[0][1], a[0][2], a[0][3], aA + ks * 896);
      ldsm4t(a[1][0], a[1][1], a[1][2], a[1][3], aA + ks * 896 + 32);
      ldsm4t(b[0], b[1], b[2], b[3], aB + ks * 896);
#pragma unroll
      for (int mt = 0; mt < 2; mt++) {
        hmma(acc[mt][0][0], acc[mt][0][1], acc[mt][0][2], acc[mt][0][3], a[mt][0], a[mt][1], a[mt][2], a[mt][3], b[0], b[1]);
        hmma(acc[mt][1][0], acc[mt][1][1], acc[mt][1][2], acc[mt][1][3], a[mt][0], a[mt][1], a[mt][2], a[mt][3], b[2], b[3]);
        hmma(acc[mt][2][0], acc[mt][2][1], acc[mt][2][2], acc[mt][2][3], a[mt][0], a[mt][1], a[mt][2], a[mt][3], kk ? c2 : c0, kk ? c3 : c1);
      }
    }
  }
  __syncwarp();
}

template <int WORDS, int J0, int STEP, int JLO, int JHI, int MUL, int OFF, bool TIE>
__device__ __forceinline__ void build_tab(uint32_t* tab, const unsigned short* kf, int lane) {
#pragma unroll
  for (int r = 0; r < WORDS / 32; r++) {
    int j = J0 + 32 * r + lane, k = j - STEP;
    int ij = TIE ? 16 * ((j + 1) >> 1) : MUL * j + OFF, ik = TIE ? 16 * ((k + 1) >> 1) : MUL * k + OFF;
    uint32_t lo = 0, hi = 0;
    if ((J0 + 32 * r >= JLO || j >= JLO) && (J0 + 32 * r + 31 <= JHI || j <= JHI)) lo = kf[ij];
    if ((J0 + 32 * r - STEP >= JLO || k >= JLO) && (J0 + 32 * r + 31 - STEP <= JHI || k <= JHI)) hi = kf[ik];
    tab[32 * r + lane] = lo | (hi << 16);
  }
}

template <int D0, int ND>
__device__ __forceinline__ void conv_A(float (&acc)[16][4], uint32_t ta, uint32_t lb) {
  uint32_t a[ND][4];
#pragma unroll
  for (int d = 0; d < ND; d++) { lds64(a[d][0], a[d][1], ta + 64 * (D0 + d)); a[d][2] = lds32(ta + 64 * (D0 + d) - 4); a[d][3] = lds32(ta + 64 * (D0 + d)); }
  constexpr int NP = (32 - D0) / 2, H = (NP + 1) / 2;
#pragma unroll
  for (int pp = 0; pp < H; pp++) {
    uint32_t b[2][4];
#pragma unroll
    for (int u = 0; u < 2; u++) { int p = pp + u * H; if (p < NP) ldsm4(b[u][0], b[u][1], b[u][2], b[u][3], lb + (2 * p - 1) * 16); }
#pragma unroll
    for (int d = 0; d < ND; d++)
#pragma unroll
      for (int u = 0; u < 2; u++) {
        int p = pp + u * H, dl = D0 + d, odd = dl & 1;
        int s = odd ? 2 * p - 1 : 2 * p, al = (s + dl) / 2;
        if (p < NP && al <= 15)
          hmma(acc[al][0], acc[al][1], acc[al][2], acc[al][3], a[d][0], a[d][1], a[d][2], a[d][3], b[u][odd ? 0 : 2], b[u][odd ? 1 : 3]);
      }
  }
}
template <int D0, int ND>
__device__ __forceinline__ void conv_B(float (&acc)[16][4], uint32_t tb, uint32_t lb) {
  uint32_t f[ND][4];
#pragma unroll
  for (int d = 0; d < ND; d++) {
    uint32_t t = tb + 64 * (D0 + d);
    f[d][0] = lds32(t); f[d][1] = lds32(t + 32); f[d][2] = lds32(t - 32); f[d][3] = lds32(t);
  }
  constexpr int NP = (16 - D0) / 2;
#pragma unroll
  for (int p = 0; p < NP; p++) {
    uint32_t b[4];
    ldsm4(b[0], b[1], b[2], b[3], lb + p * 64);
#pragma unroll
    for (int u = 0; u < 2; u++)
#pragma unroll
      for (int d = 0; d < ND; d++) {
        int al = 2 * p + u + D0 + d;
        if (al <= 15)
          hmma(acc[al][0], acc[al][2], acc[al][1], acc[al][3], f[d][0], f[d][1], f[d][2], f[d][3], b[2 * u], b[2 * u + 1]);
      }
  }
}

__global__ void __launch_bounds__(NTHR, 1)
fused_kernel(const __grid_constant__ CUtensorMap mx, const __grid_constant__ CUtensorMap mw1, const __grid_constant__ CUtensorMap mw2, const Params P) {
  extern __shared__ unsigned char smem_raw[];
  const uint32_t sb = (smem_u32(smem_raw) + 1023u) & ~1023u;
  unsigned char* sm = smem_raw + (sb - smem_u32(smem_raw));
  const int tid = threadIdx.x, lane = tid & 31;
  const int warp = __shfl_sync(0xffffffffu, tid >> 5, 0);
  const int cta = blockIdx.x, rb = cta >> 3, fs = cta & 7;
  const bool has_ch = cta < 112;
  const int g = lane >> 2, q = lane & 3;

  if (tid == 0) {
#pragma unroll
    for (int i = 0; i < 15; i++) { mbar_init(sb + M_BAR + i * 8, 1); ((uint32_t*)(sm + M_REL))[i] = 0; }
    asm volatile("fence.mbarrier_init.release.cluster;" ::: "memory");
    asm volatile("fence.proxy.async.shared::cta;" ::: "memory");
    issue_tile(0, sb, rb, fs, &mx, &mw1, &mw2);
    issue_tile(1, sb, rb, fs, &mx, &mw1, &mw2);
    issue_tile(2, sb, rb, fs, &mx, &mw1, &mw2);
    asm volatile("prefetch.tensormap [%0];" ::"l"(&mw2) : "memory");
  }

  if (warp < 8) {
    const int wg = warp >> 2;
    if (has_ch) {
      const int c = warp & 3, d = cta * 4 + c, n0 = d * NS + wg * 128 + lane * 4, n1 = n0 ^ 128;
      uint2 vla = __ldg((const uint2*)(P.logA + n0)), vai = __ldg((const uint2*)(P.Aim + n0));
      uint2 vcr = __ldg((const uint2*)(P.Cre + n0)), vci = __ldg((const uint2*)(P.Cim + n0));
      uint2 ocr = __ldg((const uint2*)(P.Cre + n1)), oci = __ldg((const uint2*)(P.Cim + n1));
      float dt = bf_round(__expf(__bfloat162float(P.logdt[d])));
      __syncthreads();
      uint32_t mx2 = __vmaxu2(__vmaxu2(__vmaxu2(vcr.x & 0x7fff7fffu, vcr.y & 0x7fff7fffu), __vmaxu2(vci.x & 0x7fff7fffu, vci.y & 0x7fff7fffu)),
                              __vmaxu2(__vmaxu2(ocr.x & 0x7fff7fffu, ocr.y & 0x7fff7fffu), __vmaxu2(oci.x & 0x7fff7fffu, oci.y & 0x7fff7fffu)));
      uint32_t mxv = __reduce_max_sync(0xffffffffu, max(mx2 & 0xffffu, mx2 >> 16));
      int e = min(max((int)(mxv >> 7), 6), 254);
      float scale = __uint_as_float((uint32_t)(259 - e) << 23);
      if (wg == 0) {
        float s = (bf_lo(vcr.x) + bf_hi(vcr.x)) + (bf_lo(vcr.y) + bf_hi(vcr.y)) + (bf_lo(ocr.x) + bf_hi(ocr.x)) + (bf_lo(ocr.y) + bf_hi(ocr.y));
#pragma unroll
        for (int o = 16; o; o >>= 1) s += __shfl_xor_sync(0xffffffffu, s, o);
        if (lane == 0) { float* ch = (float*)(sm + M_CH); ch[c] = 2.f * dt * __uint_as_float((uint32_t)(e - 5) << 23); ch[4 + c] = s * scale; }
      }
      PROF_MARK(0);
      float kacc[2][3][4];
#pragma unroll
      for (int i = 0; i < 24; i++) (&kacc[0][0][0])[i] = 0.f;
      uint32_t stg = sb + OFF_S + c * S_BLK + wg * STG_BYTES;
#pragma unroll 1
      for (int b = 0; b < 4; b++) {
        uint32_t sh = (b & 1) ? 0u : 16u;
        uint32_t wla = (b & 2) ? vla.y : vla.x, wai = (b & 2) ? vai.y : vai.x, wcr = (b & 2) ? vcr.y : vcr.x, wci = (b & 2) ? vci.y : vci.x;
        kgen_batch(kacc, bf_hi(wla << sh), bf_hi(wai << sh), bf_hi(wcr << sh) * scale, bf_hi(wci << sh) * scale, dt, stg, lane);
      }
#pragma unroll
      for (int i = 0; i < 6; i++) {
        float* a = &kacc[0][0][0] + 4 * i;
        sts128(stg + i * 512 + lane * 16, __float_as_uint(a[0]), __float_as_uint(a[1]), __float_as_uint(a[2]), __float_as_uint(a[3]));
      }
      bar_arrive(BAR_K + c, 96);
    } else {
      __syncthreads();
      const int col0 = (cta - 112) * 112;
      float* red = (float*)(sm + OFF_S);
      if (tid < 224) {
        int ck = tid % 14, rg = tid / 14;
        float s[8];
#pragma unroll
        for (int i = 0; i < 8; i++) s[i] = 0.f;
        const uint4* src = (const uint4*)(P.w1 + (size_t)rg * FF + col0 + ck * 8);
#pragma unroll 7
        for (int i = 0; i < 28; i++) {
          uint4 v = __ldg(src + (size_t)i * 16 * FF / 8);
          s[0] += bf_lo(v.x); s[1] += bf_hi(v.x); s[2] += bf_lo(v.y); s[3] += bf_hi(v.y);
          s[4] += bf_lo(v.z); s[5] += bf_hi(v.z); s[6] += bf_lo(v.w); s[7] += bf_hi(v.w);
        }
#pragma unroll
        for (int i = 0; i < 8; i++) red[rg * 112 + ck * 8 + i] = s[i];
      }
      bar_sync(BAR_C, 256);
      if (tid < 112) {
        float s = 0.f;
#pragma unroll
        for (int i = 0; i < 16; i++) s += red[i * 112 + tid];
        g_cs[col0 + tid] = s;
      }
      bar_sync(BAR_C, 256);
      if (tid == 0) red_release(&g_ctr[2 * 32]);
    }
    PROF_MARK(1);

    uint32_t h[56];
    {
      float acc[112];
#pragma unroll 1
      for (int kb = 0; kb < 7; kb++) {
        int s = kb % 3;
        mbar_wait(sb + M_BAR + kb * 8, 0);
        uint64_t da = mkdesc(sb + OFF_A + s * A_STAGE + wg * 8192, 16, 1024, 1);
        uint64_t db = mkdesc(sb + OFF_W + s * W_STAGE, 4096, 512, 2);
        wg_fence();
#pragma unroll
        for (int k = 0; k < 4; k++) wgmma_ss_n224(acc, da + k * 2, db + k * 64, (kb | k) != 0);
        wg_commit();
        wg_wait0();
        release_tile(kb, sb, rb, fs, lane, &mx, &mw1, &mw2);
      }
      bar_arrive(BAR_G1, 384);
      PROF_MARK(2);
      bar_sync(BAR_STAT, 384);
      if (EXP & 8) bar_sync(BAR_CONV, 384);
      const int row = wg * 64 + (warp & 3) * 16 + g;
      float4 st0 = ((const float4*)(sm + M_ROW))[row], st1 = ((const float4*)(sm + M_ROW))[row + 8];
      float r0 = st0.w, k0 = -st0.w * st0.z, r1 = st1.w, k1 = -st1.w * st1.z;
#pragma unroll
      for (int i = 0; i < 28; i++) {
        float4 cv = ((const float4*)(sm + M_COL))[4 * i + q];
        float v[4] = {fmaf(r0, acc[4 * i], fmaf(k0, cv.x, cv.y)), fmaf(r0, acc[4 * i + 1], fmaf(k0, cv.z, cv.w)),
                      fmaf(r1, acc[4 * i + 2], fmaf(k1, cv.x, cv.y)), fmaf(r1, acc[4 * i + 3], fmaf(k1, cv.z, cv.w))};
#pragma unroll
        for (int e = 0; e < 4; e++) {
          float u = v[e] * fmaf(v[e] * v[e], 0.035677408136300125f, 0.7978845608028654f);
          float hh = 0.5f * v[e];
          v[e] = fmaf(hh, tanhf_fast(u), hh);
        }
        h[2 * i] = pack_bf2(v[0], v[1]);
        h[2 * i + 1] = pack_bf2(v[2], v[3]);
      }
    }
    const uint32_t tag = (*(const volatile uint32_t*)(sm + M_EPOCH) + 1u) << 16;
    PROF_MARK(3);
    if (!(EXP & 8)) bar_sync(BAR_CONV, 384);
    PROF_MARK(4);

    float o[28];
    uint32_t sum[4][4], inb[4][4];
#pragma unroll
    for (int v = 0; v < 4; v++)
#pragma unroll
      for (int k = 0; k < 4; k++) sum[v][k] = 0u;
    const uint4* rbase = g_part + (size_t)((rb * 8 + fs) * 8) * 1024 + tid;
    uint4* wbase = g_part + (size_t)(rb * 64 + fs) * 1024 + tid;
    auto fetch = [&](int p) {
      const uint4* s = rbase + ((fs - 1 - p) & 7) * 1024;
#pragma unroll
      for (int v = 0; v < 4; v++) ld_b128(inb[v], s + v * 256);
    };
    auto consume = [&](int p) {
      const uint4* s = rbase + ((fs - 1 - p) & 7) * 1024;
#pragma unroll
      for (int v = 0; v < 4; v++) {
        for (int n = 0; (inb[v][3] & 0xffff0000u) != tag; n++) {
          if (n > (1 << 20)) __trap();
          ld_b128(inb[v], s + v * 256);
        }
#pragma unroll
        for (int k = 0; k < 4; k++) sum[v][k] = hadd2(sum[v][k], inb[v][k]);
      }
    };
    if (wg == 1 && !(EXP & 4)) bar_arrive(BAR_PP, 256);
#pragma unroll 1
    for (int p = 0; p < 8; p++) {
      mbar_wait(sb + M_BAR + (7 + p) * 8, 0);
      uint64_t db = mkdesc(w2_slot(sb, p), 16, 1024, 1);
      if (!(EXP & 4)) bar_sync(BAR_PP + wg, 256);
      wg_fence();
#pragma unroll
      for (int k = 0; k < 14; k++) wgmma_rs_n56(o, h[4 * k], h[4 * k + 1], h[4 * k + 2], h[4 * k + 3], db + k * 128, k != 0);
      wg_commit();
      if (!(EXP & 4) && (wg == 0 || p < 7)) bar_arrive(BAR_PP + (wg ^ 1), 256);
      wg_wait0();
      if (p < 7) {
        release_tile(7 + p, sb, rb, fs, lane, &mx, &mw1, &mw2);
        uint4* dst = wbase + ((fs + 1 + p) & 7) * 8192;
#pragma unroll
        for (int v = 0; v < 4; v++)
          if (!(EXP & 1)) st_b128(dst + v * 256, pack_h2(o[7 * v], o[7 * v + 1]), pack_h2(o[7 * v + 2], o[7 * v + 3]), pack_h2(o[7 * v + 4], o[7 * v + 5]),
                  (pack_h2(o[7 * v + 6], 0.f) & 0xffffu) | tag);
      }
      if (p >= 2 && !(EXP & 2)) consume(p - 2);
      if (p >= 1 && !(EXP & 2)) fetch(p - 1);
    }
    PROF_MARK(5);
    if (!(EXP & 2)) consume(6);
    PROF_MARK(6);
    bar_sync(BAR_FIN, 384);
    {
      const int row = rb * 128 + wg * 64 + (warp & 3) * 16 + g;
      uint32_t* op = (uint32_t*)(P.out + (size_t)row * DM + fs * 56 + 2 * q);
      const uint32_t* b2p = (const uint32_t*)(P.b2 + fs * 56 + 2 * q);
#pragma unroll
      for (int v = 0; v < 4; v++)
#pragma unroll
        for (int k = 0; k < 7; k++) {
          __half2 hv = *reinterpret_cast<__half2*>(&sum[v][k >> 1]);
          o[7 * v + k] += (k & 1) ? __high2float(hv) : __low2float(hv);
        }
#pragma unroll
      for (int i = 0; i < 7; i++) {
        uint4 xs = ((const uint4*)(sm + OFF_S))[i * 256 + tid];
        uint32_t bb = __ldg(b2p + 4 * i);
        float r[4];
#pragma unroll
        for (int e = 0; e < 4; e++) {
          float ho = 0.5f * (o[4 * i + e] + ((e & 1) ? bf_hi(bb) : bf_lo(bb)));
          float gt = fmaf(ho, tanhf_fast(ho), ho);
          uint32_t xw = (e & 2) ? xs.z : xs.x, sw = (e & 2) ? xs.w : xs.y;
          r[e] = (e & 1) ? fmaf(bf_hi(sw), gt, bf_hi(xw)) : fmaf(bf_lo(sw), gt, bf_lo(xw));
        }
        op[4 * i] = pack_bf2(r[0], r[1]);
        op[4 * i + 8 * DM / 2] = pack_bf2(r[2], r[3]);
      }
    }
    PROF_MARK(7);
  } else {
    const int v = warp - 8, st = tid - 256;
    unsigned epoch = 0;
    if (st == 0) epoch = atomicAdd(&g_ctr[0], 1u) >> 7;
    {
      const int i = 4 * v + (lane >> 3), j = lane & 7, t = rb * 128 + 8 * i + fs;
      uint32_t xv[28];
      const uint4* src = (const uint4*)(P.x + (size_t)t * DM) + j;
#pragma unroll
      for (int k = 0; k < 7; k++) { uint4 u = __ldg(src + 8 * k); xv[4 * k] = u.x; xv[4 * k + 1] = u.y; xv[4 * k + 2] = u.z; xv[4 * k + 3] = u.w; }
      __syncthreads();
      float s0 = 0.f, s1 = 0.f;
#pragma unroll
      for (int k = 0; k < 28; k++) { s0 += bf_lo(xv[k]); s1 += bf_hi(xv[k]); }
      s0 += s1;
#pragma unroll
      for (int o = 1; o < 8; o <<= 1) s0 += __shfl_xor_sync(0xffffffffu, s0, o);
      float mu = s0 * (1.f / DM);
      float q0 = 0.f, q1 = 0.f;
#pragma unroll
      for (int k = 0; k < 28; k++) { float a = bf_lo(xv[k]) - mu, b = bf_hi(xv[k]) - mu; q0 = fmaf(a, a, q0); q1 = fmaf(b, b, q1); }
      q0 += q1;
#pragma unroll
      for (int o = 1; o < 8; o <<= 1) q0 += __shfl_xor_sync(0xffffffffu, q0, o);
      float m1 = bf_round(mu);
      float d1 = bf_round(sqrtf(bf_round(bf_round(q0 * (1.f / DM)) + 1e-5f)));
      float i1 = 1.f / d1;
      uint32_t m2 = pack_bf2(m1, m1);
      s0 = 0.f; s1 = 0.f; q0 = 0.f; q1 = 0.f;
      uint32_t tb = sb + OFF_S + v * S_BLK + 2 * STG_BYTES + (i & 3) * 1024 + (2 * v + (i & 1)) * 16 + j * 16;
#pragma unroll
      for (int k = 0; k < 7; k++) {
        uint32_t hv[4];
#pragma unroll
        for (int e = 0; e < 4; e++) {
          uint32_t dd = bsub2(xv[4 * k + e], m2);
          uint32_t xn = pack_bf2(bf_lo(dd) * i1, bf_hi(dd) * i1);
          float a = bf_lo(xn), b = bf_hi(xn);
          s0 += a; s1 += b; q0 = fmaf(a, a, q0); q1 = fmaf(b, b, q1);
          hv[e] = pack_h2(a, b);
        }
        sts128(tb + k * 128, hv[0], hv[1], hv[2], hv[3]);
      }
      s0 += s1; q0 += q1;
#pragma unroll
      for (int o = 1; o < 8; o <<= 1) { s0 += __shfl_xor_sync(0xffffffffu, s0, o); q0 += __shfl_xor_sync(0xffffffffu, q0, o); }
      float mu2 = s0 * (1.f / DM);
      float var2 = fmaxf(fmaf(-mu2, mu2, q0 * (1.f / DM)), 0.f);
      float d2 = bf_round(sqrtf(bf_round(bf_round(var2) + 1e-5f)));
      if (j == 0) g_stats[t] = make_float4(m1, i1, fmaf(bf_round(mu2), d1, m1), 1.f / (d1 * d2));
      if (st == 0) *(volatile uint32_t*)(sm + M_EPOCH) = epoch;
      bar_sync(BAR_S, 128);
      epoch = *(const volatile uint32_t*)(sm + M_EPOCH);
      const int mi = lane >> 3, r = lane & 7, ri = 4 * (r >> 1) + 2 * (mi & 1) + (r & 1);
      uint32_t la = sb + OFF_S + (ri >> 2) * S_BLK + 2 * STG_BYTES + (ri & 3) * 1024 + r * 16 + (14 * v + (mi >> 1)) * 16;
      __half* dst = g_xnT + (size_t)(112 * v + g) * SEQ + fs * 256 + 16 * rb + 4 * q;
#pragma unroll
      for (int k = 0; k < 7; k++) {
        uint32_t r0, r1, r2, r3;
        ldsm4t(r0, r1, r2, r3, la + k * 32);
        *(uint2*)(dst + (size_t)(16 * k) * SEQ) = make_uint2(r0, r1);
        *(uint2*)(dst + (size_t)(16 * k + 8) * SEQ) = make_uint2(r2, r3);
      }
      bar_sync(BAR_S, 128);
      if (st == 0) red_release(&g_ctr[1 * 32]);
    }
    PROF_MARK(0);
    const int d = cta * 4 + v;
    unsigned char* blk = sm + OFF_S + v * S_BLK;
    const uint32_t bs = sb + OFF_S + v * S_BLK;
    float post = 0.f;
    uint32_t kdiag = 0;
    if (has_ch) {
      bar_sync(BAR_K + v, 96);
      PROF_MARK(1);
      unsigned short* kf = (unsigned short*)(blk + B_KFULL);
      post = ((const float*)(sm + M_CH))[v];
      const int pi[3] = {2 * q + 1, q < 2 ? 258 + 4 * q : 4 + 256 * q, 1032 + 512 * q};
      const int ps[3] = {1, q < 2 ? 2 : 4, 256};
#pragma unroll
      for (int i = 0; i < 6; i++) {
        float4 a = ((const float4*)blk)[i * 32 + lane], b = ((const float4*)(blk + STG_BYTES))[i * 32 + lane];
        uint32_t lo = pack_h2(a.x + b.x, a.y + b.y), hi = pack_h2(a.z + b.z, a.w + b.w);
        int mt = i / 3, nt = i % 3, p0 = 8 * (16 * mt + g) + pi[nt];
        if (nt < 2 || q < 2) {
          kf[p0] = (unsigned short)lo; kf[p0 + ps[nt]] = (unsigned short)(lo >> 16);
          kf[p0 + 64] = (unsigned short)hi; kf[p0 + 64 + ps[nt]] = (unsigned short)(hi >> 16);
        }
      }
      __syncwarp();
      if (lane == 0) { kf[0] = (unsigned short)pack_h2(((const float*)(sm + M_CH))[4 + v], 0.f); kf[257] = kf[256]; kf[514] = kf[512]; }
      kdiag = kf[1024];
      __syncwarp();
      uint32_t* tab = (uint32_t*)(blk + B_TAB);
      build_tab<96, -14, 2, 0, 64, 4, 0, false>(tab + T_A0, kf, lane);
      build_tab<96, -14, 2, 0, 64, 4, 1, false>(tab + T_A1, kf, lane);
      build_tab<96, -14, 2, 0, 63, 4, 3, false>(tab + T_A3, kf, lane);
      build_tab<160, -14, 2, 0, 128, 4, 2, false>(tab + T_A2, kf, lane);
      build_tab<96, 50, 2, 64, 127, 4, 4, false>(tab + T_A4, kf, lane);
      build_tab<96, 50, 1, 64, 127, 8, 8, false>(tab + T_B5, kf, lane);
      build_tab<96, 50, 1, 64, 127, 8, 4, false>(tab + T_B3, kf, lane);
      build_tab<160, 114, 1, 128, 255, 8, 8, false>(tab + T_B7, kf, lane);
      build_tab<160, 114, 1, 128, 255, 8, 4, true>(tab + T_BT, kf, lane);
      __syncwarp();
    }
    PROF_MARK(2);
    if (lane == 0) { wait_counter(&g_ctr[1 * 32], (epoch + 1) * 128u); }
    __syncwarp();
    PROF_MARK(3);
    uint32_t R[8][4];
    if (has_ch) {
      const uint4* src = (const uint4*)(g_xnT + (size_t)d * SEQ) + lane;
#pragma unroll
      for (int f = 0; f < 8; f++) { uint4 u = __ldcg(src + f * 32); R[f][0] = u.x; R[f][1] = u.y; R[f][2] = u.z; R[f][3] = u.w; }
    }
    ((float4*)(sm + M_ROW))[st] = __ldcg(&g_stats[rb * 128 + st]);
    if (lane == 0) wait_counter(&g_ctr[2 * 32], (epoch + 1) * 16u);
    __syncwarp();
    if (st < 112) {
      float2 cs = __ldcg((const float2*)(g_cs + fs * 224) + st);
      uint32_t bb = __ldg((const uint32_t*)(P.b1 + fs * 224) + st);
      ((float4*)(sm + M_COL))[st] = make_float4(cs.x, bf_lo(bb), cs.y, bf_hi(bb));
    }
    bar_arrive(BAR_STAT, 384);
    if (has_ch) {
      uint32_t Q[19][4];
#pragma unroll
      for (int f = 0; f < 8; f++) {
        uint32_t pv = __shfl_up_sync(0xffffffffu, R[f][3], 1);
        if (lane == 0) pv = 0;
#pragma unroll
        for (int k = 0; k < 4; k++) {
          Q[11 + f][k] = R[f][k];
          Q[3 + f][k] = __byte_perm(k ? R[f][k - 1] : pv, R[f][k], 0x5432);
          if (f >= 5) Q[f - 5][k] = k ? R[f][k - 1] : pv;
        }
      }
      uint32_t pa = bs + 16 + lane * 16;
#pragma unroll
      for (int f = 0; f < 12; f++) sts128(pa + B_P + f * PP, Q[7 + f][0], Q[7 + f][1], Q[7 + f][2], Q[7 + f][3]);
      if (lane < 20) sts128(bs + lane * PP, 0u, 0u, 0u, 0u);
      uint32_t B2[14][4], T3[12][4], V5[9][4];
#pragma unroll
      for (int k = 0; k < 4; k++) {
#pragma unroll
        for (int f = 0; f < 14; f++) B2[f][k] = hadd2(Q[f][k], Q[f + 1][k]);
#pragma unroll
        for (int f = 0; f < 12; f++) T3[f][k] = hadd2(B2[f + 2][k], Q[f + 4][k]);
#pragma unroll
        for (int f = 0; f < 9; f++) V5[f][k] = hadd2(B2[f][k], T3[f][k]);
      }
#pragma unroll
      for (int f = 0; f < 8; f++) {
        sts128(pa + B_V3 + f * PP, T3[f + 4][0], T3[f + 4][1], T3[f + 4][2], T3[f + 4][3]);
        if (lane < 24) sts128(bs + B_V5 + f * P5 + lane * 16, V5[f + 1][0], V5[f + 1][1], V5[f + 1][2], V5[f + 1][3]);
        if (lane < 16) sts128(bs + B_V7 + f * P7 + lane * 16, hadd2(V5[f][0], B2[f + 5][0]), hadd2(V5[f][1], B2[f + 5][1]), hadd2(V5[f][2], B2[f + 5][2]), hadd2(V5[f][3], B2[f + 5][3]));
      }
      __syncwarp();
    }
    PROF_MARK(4);
    bar_sync(BAR_G1, 384);
    PROF_MARK(5);
    if (has_ch) {
      float acc[16][4];
#pragma unroll
      for (int i = 0; i < 16; i++) { acc[i][0] = 0.f; acc[i][1] = 0.f; acc[i][2] = 0.f; acc[i][3] = 0.f; }
      const int mi = lane >> 3, n = lane & 7;
      const uint32_t tA = bs + B_TAB + (14 + 2 * g - 4 * q) * 4, tB = bs + B_TAB + (g - 2 * q) * 4;
      const uint32_t lA = bs + ((n >> 1) + 4 * (mi & 1)) * PP + 16 + ((mi >> 1) + (n & 1)) * 16;
      const int r8 = 4 * (n & 1) + (n >> 1);
#pragma unroll 1
      for (int s = 0; s < 3; s++) conv_A<0, 5>(acc, tA + s * 96 * 4, lA + (s == 2 ? 1 : 4 - s) * PP);
      conv_A<0, 9>(acc, tA + T_A2 * 4, lA + 2 * PP);
      conv_A<4, 5>(acc, tA + (T_A4 - 64) * 4, lA + B_V3);
      {
        uint32_t a0 = g == 2 * q ? kdiag : (g == 2 * q + 1 ? kdiag << 16 : 0u);
        const uint32_t lX = lA + PP + (mi >> 1) * 16;
#pragma unroll
        for (int p = 0; p < 4; p++) {
          uint32_t b[4];
          ldsm4(b[0], b[1], b[2], b[3], lX + p * 64);
          hmma(acc[8 + 2 * p][0], acc[8 + 2 * p][1], acc[8 + 2 * p][2], acc[8 + 2 * p][3], a0, 0u, 0u, a0, b[0], b[1]);
          hmma(acc[9 + 2 * p][0], acc[9 + 2 * p][1], acc[9 + 2 * p][2], acc[9 + 2 * p][3], a0, 0u, 0u, a0, b[2], b[3]);
        }
      }
#pragma unroll 1
      for (int s = 0; s < 2; s++) conv_B<4, 5>(acc, tB + (T_B5 - 50 + s * 96) * 4, s ? bs + B_V3 + r8 * PP + 16 + mi * 16 : bs + B_V5 + r8 * P5 + mi * 16);
#pragma unroll 1
      for (int s = 0; s < 2; s++) conv_B<8, 8>(acc, tB + (T_B7 - 114 + s * 160) * 4, s ? bs + B_P + r8 * PP + 16 + mi * 16 : bs + B_V7 + r8 * P7 + mi * 16);
      uint2* yd = g_y + (size_t)d * 512 + lane;
#pragma unroll
      for (int i = 0; i < 16; i++) yd[i * 32] = make_uint2(pack_bf2(acc[i][0] * post, acc[i][1] * post), pack_bf2(acc[i][2] * post, acc[i][3] * post));
      bar_arrive(BAR_CONV, 384);
      PROF_MARK(6);
      __syncwarp();
      if (lane == 0) red_release(&g_ctr[(8 + cta / 14) * 32]);
    } else {
      bar_arrive(BAR_CONV, 384);
    }
    {
      const int row = v * 16 + g;
      const uint32_t* xp = (const uint32_t*)(P.x + (size_t)(rb * 128 + row) * DM + fs * 56 + 2 * q);
      const uint32_t* dp = (const uint32_t*)(P.Dskip + fs * 56 + 2 * q);
      uint32_t xw[7][4], tw[7][4];
      uint32_t m2[4]; float i1[4];
#pragma unroll
      for (int k = 0; k < 4; k++) { float4 s4 = ((const float4*)(sm + M_ROW))[row + (k & 1) * 8 + (k >> 1) * 64]; m2[k] = pack_bf2(s4.x, s4.x); i1[k] = s4.y; }
#pragma unroll
      for (int i = 0; i < 7; i++)
#pragma unroll
        for (int k = 0; k < 4; k++) xw[i][k] = __ldg(xp + 4 * i + ((k & 1) * 8 + (k >> 1) * 64) * (DM / 2));
#pragma unroll
      for (int i = 0; i < 7; i++) {
        uint32_t dk = __ldg(dp + 4 * i);
#pragma unroll
        for (int k = 0; k < 4; k++) {
          uint32_t dd = bsub2(xw[i][k], m2[k]);
          tw[i][k] = bmul2(pack_bf2(bf_lo(dd) * i1[k], bf_hi(dd) * i1[k]), dk);
        }
      }
      if (lane == 0) wait_counter(&g_ctr[(8 + fs) * 32], (epoch + 1) * 56u);
      bar_sync(BAR_S, 128);
      PROF_MARK(7);
      const uint32_t* yp = (const uint32_t*)(g_y + (size_t)(fs * 56 + 2 * q) * 512 + rb * 32 + 8 * v + (g & 3)) + (g >> 2);
#pragma unroll
      for (int i = 0; i < 7; i++) {
        uint32_t y00 = __ldcg(yp + (8 * i) * 1024), y01 = __ldcg(yp + (8 * i + 1) * 1024);
        uint32_t y10 = __ldcg(yp + (8 * i) * 1024 + 8), y11 = __ldcg(yp + (8 * i + 1) * 1024 + 8);
        uint32_t a = sb + OFF_S + (i * 256 + st) * 16;
        sts128(a, xw[i][0], badd2(__byte_perm(y00, y01, 0x5410), tw[i][0]), xw[i][1], badd2(__byte_perm(y10, y11, 0x5410), tw[i][1]));
        sts128(a + 2048, xw[i][2], badd2(__byte_perm(y00, y01, 0x7632), tw[i][2]), xw[i][3], badd2(__byte_perm(y10, y11, 0x7632), tw[i][3]));
      }
      bar_arrive(BAR_FIN, 384);
      PROF_MARK(8);
    }
  }
}

typedef CUresult (*EncodeFn)(CUtensorMap*, CUtensorMapDataType, cuuint32_t, void*, const cuuint64_t*, const cuuint64_t*, const cuuint32_t*,
                             const cuuint32_t*, CUtensorMapInterleave, CUtensorMapSwizzle, CUtensorMapL2promotion, CUtensorMapFloatOOBfill);

}

extern "C" void kernel_launch(void* const* d_in, const int* in_sizes, int n_in, void* d_out, int out_size) {
  (void)in_sizes; (void)n_in; (void)out_size;
  static EncodeFn enc = nullptr;
  if (!enc) {
    void* fn = nullptr;
    cudaDriverEntryPointQueryResult qr;
    cudaGetDriverEntryPoint("cuTensorMapEncodeTiled", &fn, cudaEnableDefault, &qr);
    enc = (EncodeFn)fn;
    cudaFuncSetAttribute(fused_kernel, cudaFuncAttributeMaxDynamicSharedMemorySize, SMEM_BYTES);
  }
  typedef const __nv_bfloat16* bp;
  Params P;
  P.x = (bp)d_in[0]; P.logA = (bp)d_in[1]; P.Aim = (bp)d_in[2]; P.Cre = (bp)d_in[3]; P.Cim = (bp)d_in[4];
  P.logdt = (bp)d_in[5]; P.Dskip = (bp)d_in[6]; P.w1 = (bp)d_in[8]; P.b1 = (bp)d_in[9]; P.b2 = (bp)d_in[11];
  P.out = (__nv_bfloat16*)d_out;
  CUtensorMap mx, mw1, mw2;
  {
    cuuint64_t dims[2] = {DM, SEQ}, str[1] = {DM * 2}; cuuint32_t box[2] = {64, 128}, es[2] = {1, 1};
    enc(&mx, CU_TENSOR_MAP_DATA_TYPE_BFLOAT16, 2, d_in[0], dims, str, box, es, CU_TENSOR_MAP_INTERLEAVE_NONE, CU_TENSOR_MAP_SWIZZLE_128B,
        CU_TENSOR_MAP_L2_PROMOTION_L2_128B, CU_TENSOR_MAP_FLOAT_OOB_FILL_NONE);
  }
  {
    cuuint64_t dims[3] = {32, DM, FF / 32}, str[2] = {FF * 2, 64}; cuuint32_t box[3] = {32, 64, 7}, es[3] = {1, 1, 1};
    enc(&mw1, CU_TENSOR_MAP_DATA_TYPE_BFLOAT16, 3, d_in[8], dims, str, box, es, CU_TENSOR_MAP_INTERLEAVE_NONE, CU_TENSOR_MAP_SWIZZLE_64B,
        CU_TENSOR_MAP_L2_PROMOTION_L2_128B, CU_TENSOR_MAP_FLOAT_OOB_FILL_NONE);
  }
  {
    cuuint64_t dims[2] = {DM, FF}, str[1] = {DM * 2}; cuuint32_t box[2] = {64, 224}, es[2] = {1, 1};
    enc(&mw2, CU_TENSOR_MAP_DATA_TYPE_BFLOAT16, 2, d_in[10], dims, str, box, es, CU_TENSOR_MAP_INTERLEAVE_NONE, CU_TENSOR_MAP_SWIZZLE_128B,
        CU_TENSOR_MAP_L2_PROMOTION_L2_128B, CU_TENSOR_MAP_FLOAT_OOB_FILL_NONE);
  }
  fused_kernel<<<NCTA, NTHR, SMEM_BYTES, cudaStreamPerThread>>>(mx, mw1, mw2, P);
}
```

```cpp
#include <cuda_runtime.h>
#include <cuda_bf16.h>
#include <cuda_fp16.h>
#include <cuda.h>
#include <stdint.h>
#include <initializer_list>

namespace {

constexpr int SEQ = 2048, DM = 448, FF = 1792, NS = 256;
constexpr int NCTA = 128, NTHR = 384;

__device__ __align__(128) __half g_xnT[DM * SEQ];
__device__ __align__(128) float2 g_stats[SEQ];
__device__ __align__(128) float g_cs[2 * FF];
__device__ __align__(128) uint32_t g_y[DM * 1024];
__device__ __align__(128) uint4 g_part[NCTA * 3 * 1024];
__device__ __align__(128) unsigned g_done[32];
__device__ unsigned g_ticket;

constexpr int A_STAGE = 16384, W_STAGE = 28672;
constexpr int OFF_A = 0;
constexpr int OFF_W = 3 * A_STAGE;
constexpr int OFF_S = OFF_W + 3 * W_STAGE;
constexpr int S_BLK = 21504;
constexpr int OFF_M = OFF_S + 4 * S_BLK;
constexpr int M_BAR = OFF_M, MB_E = OFF_M + 192, M_EPOCH = OFF_M + 248;
constexpr int MB_W2 = M_BAR + 56, MB_CS = M_BAR + 120, MB_PASS = M_BAR + 128, MB_FREE = M_BAR + 152, MB_H = M_BAR + 160, MB_X = M_BAR + 168, MB_Y = M_BAR + 176, MB_R = M_BAR + 184;
constexpr int M_B2 = OFF_M + 3072;
constexpr int M_COL = OFF_M + 256, M_ROW = OFF_M + 2048;
constexpr int SMEM_BYTES = OFF_M + 4096 + 1024;
constexpr int STG_BYTES = 5376;
constexpr int B_TAB = 17152, B_XT = 11264;
constexpr int PP = 544, P5 = 400, P7 = 272;
constexpr int B_P = 0, B_V3 = 12 * PP, B_V5 = B_V3 + 8 * PP, B_V7 = B_V5 + 8 * P5;
constexpr int T_A0 = 0, T_A1 = 96, T_A3 = 208, T_A2 = 304, T_A4 = 464, T_B3 = 560, T_B5 = 664, T_B7 = 760, T_BT = 908;

constexpr int BAR_INIT = 0, BAR_S = 1, BAR_K = 2, BAR_K2 = 3, BAR_STAT = 6, BAR_G1 = 7, BAR_PP = 10  , BAR_C = 12, BAR_FIN = 13  ;
constexpr int OFF_H = 0, OFF_XT = 2 * W_STAGE, OFF_HL = OFF_XT + A_STAGE, OFF_YT = OFF_S + 2 * W_STAGE;

__device__ __forceinline__ uint32_t smem_u32(const void* p) { return (uint32_t)__cvta_generic_to_shared(p); }
__device__ __forceinline__ void bar_sync(int id, int n) { asm volatile("bar.sync %0, %1;" ::"r"(id), "r"(n) : "memory"); }
__device__ __forceinline__ void bar_arrive(int id, int n) { asm volatile("bar.arrive %0, %1;" ::"r"(id), "r"(n) : "memory"); }
__device__ __forceinline__ void mbar_init(uint32_t bar, int cnt) { asm volatile("mbarrier.init.shared::cta.b64 [%0], %1;" ::"r"(bar), "r"(cnt) : "memory"); }
__device__ __forceinline__ void mbar_expect(uint32_t bar, int bytes) { asm volatile("mbarrier.arrive.expect_tx.shared::cta.b64 _, [%0], %1;" ::"r"(bar), "r"(bytes) : "memory"); }
__device__ __forceinline__ void mbar_wait(uint32_t bar, int parity) {
  for (int n = 0;; n++) {
    uint32_t ok;
    asm volatile("{ .reg .pred p; mbarrier.try_wait.parity.shared::cta.b64 p, [%1], %2; selp.u32 %0, 1, 0, p; }" : "=r"(ok) : "r"(bar), "r"(parity) : "memory");
    if (ok || n > (1 << 18)) break;
  }
}
__device__ __forceinline__ void tma2d(uint32_t dst, const CUtensorMap* m, int c0, int c1, uint32_t bar) {
  asm volatile("cp.async.bulk.tensor.2d.shared::cluster.global.mbarrier::complete_tx::bytes [%0], [%1, {%3, %4}], [%2];"
               ::"r"(dst), "l"(m), "r"(bar), "r"(c0), "r"(c1) : "memory");
}
__device__ __forceinline__ void tma3d(uint32_t dst, const CUtensorMap* m, int c0, int c1, int c2, uint32_t bar) {
  asm volatile("cp.async.bulk.tensor.3d.shared::cluster.global.mbarrier::complete_tx::bytes [%0], [%1, {%3, %4, %5}], [%2];"
               ::"r"(dst), "l"(m), "r"(bar), "r"(c0), "r"(c1), "r"(c2) : "memory");
}
__device__ __forceinline__ void tma4d(uint32_t dst, const CUtensorMap* m, int c0, int c1, int c2, int c3, uint32_t bar) {
  asm volatile("cp.async.bulk.tensor.4d.shared::cluster.global.mbarrier::complete_tx::bytes [%0], [%1, {%3, %4, %5, %6}], [%2];"
               ::"r"(dst), "l"(m), "r"(bar), "r"(c0), "r"(c1), "r"(c2), "r"(c3) : "memory");
}
__device__ __forceinline__ uint64_t mkdesc(uint32_t addr, uint32_t lbo, uint32_t sbo, int swz) {
  return (uint64_t)((addr & 0x3FFFF) >> 4) | ((uint64_t)(lbo >> 4) << 16) | ((uint64_t)(sbo >> 4) << 32) | ((uint64_t)swz << 62);
}
__device__ __forceinline__ void wg_fence() { asm volatile("wgmma.fence.sync.aligned;" ::: "memory"); }
__device__ __forceinline__ void wg_commit() { asm volatile("wgmma.commit_group.sync.aligned;" ::: "memory"); }
template <int N> __device__ __forceinline__ void fence_regs(float (&a)[N]) {
#pragma unroll
  for (int i = 0; i < N; i++) asm volatile("" : "+f"(a[i])::"memory");
}
__device__ __forceinline__ void wg_wait2() { asm volatile("wgmma.wait_group.sync.aligned 2;" ::: "memory"); }
__device__ __forceinline__ void wg_wait1() { asm volatile("wgmma.wait_group.sync.aligned 1;" ::: "memory"); }
__device__ __forceinline__ void wg_wait0() { asm volatile("wgmma.wait_group.sync.aligned 0;" ::: "memory"); }
__device__ __forceinline__ void hmma(float& c0, float& c1, float& c2, float& c3, uint32_t a0, uint32_t a1, uint32_t a2, uint32_t a3, uint32_t b0, uint32_t b1) {
  asm("mma.sync.aligned.m16n8k16.row.col.f32.f16.f16.f32 {%0,%1,%2,%3}, {%4,%5,%6,%7}, {%8,%9}, {%0,%1,%2,%3};"
      : "+f"(c0), "+f"(c1), "+f"(c2), "+f"(c3) : "r"(a0), "r"(a1), "r"(a2), "r"(a3), "r"(b0), "r"(b1));
}
__device__ __forceinline__ void ones_mma(float (&c)[4], uint32_t b0, uint32_t b1) {
  asm("mma.sync.aligned.m16n8k16.row.col.f32.bf16.bf16.f32 {%0,%1,%2,%3}, {%4,%4,%4,%4}, {%5,%6}, {%0,%1,%2,%3};"
      : "+f"(c[0]), "+f"(c[1]), "+f"(c[2]), "+f"(c[3]) : "r"(0x3f803f80u), "r"(b0), "r"(b1));
}
__device__ __forceinline__ void red_hint(unsigned* p) { asm volatile("red.relaxed.gpu.global.add.u32 [%0], 1;" ::"l"(p) : "memory"); }
__device__ __forceinline__ void ldsm4(uint32_t& r0, uint32_t& r1, uint32_t& r2, uint32_t& r3, uint32_t addr) {
  asm volatile("ldmatrix.sync.aligned.m8n8.x4.shared.b16 {%0,%1,%2,%3}, [%4];" : "=r"(r0), "=r"(r1), "=r"(r2), "=r"(r3) : "r"(addr));
}
__device__ __forceinline__ void ldsm4t(uint32_t& r0, uint32_t& r1, uint32_t& r2, uint32_t& r3, uint32_t addr) {
  asm volatile("ldmatrix.sync.aligned.m8n8.x4.trans.shared.b16 {%0,%1,%2,%3}, [%4];" : "=r"(r0), "=r"(r1), "=r"(r2), "=r"(r3) : "r"(addr));
}
__device__ __forceinline__ void sts128(uint32_t addr, uint32_t a, uint32_t b, uint32_t c, uint32_t d) {
  asm volatile("st.shared.v4.b32 [%0], {%1,%2,%3,%4};" ::"r"(addr), "r"(a), "r"(b), "r"(c), "r"(d) : "memory");
}
__device__ __forceinline__ uint32_t lds32(uint32_t addr) { uint32_t v; asm volatile("ld.shared.b32 %0, [%1];" : "=r"(v) : "r"(addr)); return v; }
__device__ __forceinline__ float4 lds128f(uint32_t addr) { float4 v; asm volatile("ld.shared.v4.f32 {%0,%1,%2,%3}, [%4];" : "=f"(v.x), "=f"(v.y), "=f"(v.z), "=f"(v.w) : "r"(addr)); return v; }
__device__ __forceinline__ void lds64(uint32_t& a, uint32_t& b, uint32_t addr) { asm volatile("ld.shared.v2.b32 {%0,%1}, [%2];" : "=r"(a), "=r"(b) : "r"(addr)); }
__device__ __forceinline__ uint32_t pack_h2(float lo, float hi) { uint32_t r; asm("cvt.rn.f16x2.f32 %0, %1, %2;" : "=r"(r) : "f"(hi), "f"(lo)); return r; }
__device__ __forceinline__ uint32_t pack_bf2(float lo, float hi) { uint32_t r; asm("cvt.rn.bf16x2.f32 %0, %1, %2;" : "=r"(r) : "f"(hi), "f"(lo)); return r; }
__device__ __forceinline__ float bf_lo(uint32_t v) { return __uint_as_float(v << 16); }
__device__ __forceinline__ float bf_hi(uint32_t v) { return __uint_as_float(v & 0xffff0000u); }
__device__ __forceinline__ float bf_round(float x) { return __uint_as_float(pack_bf2(0.f, x)); }
__device__ __forceinline__ uint32_t hadd2(uint32_t a, uint32_t b) { uint32_t r; asm("add.rn.f16x2 %0, %1, %2;" : "=r"(r) : "r"(a), "r"(b)); return r; }
__device__ __forceinline__ uint32_t hmul2(uint32_t a, uint32_t b) { uint32_t r; asm("mul.rn.f16x2 %0, %1, %2;" : "=r"(r) : "r"(a), "r"(b)); return r; }
__device__ __forceinline__ uint32_t hfma2(uint32_t a, uint32_t b, uint32_t c) { uint32_t r; asm("fma.rn.f16x2 %0, %1, %2, %3;" : "=r"(r) : "r"(a), "r"(b), "r"(c)); return r; }
__device__ __forceinline__ float ex2f(float x) { float r; asm("ex2.approx.ftz.f32 %0, %1;" : "=f"(r) : "f"(x)); return r; }
__device__ __forceinline__ uint32_t gelu2(float lo, float hi) {
  uint32_t r;
  asm("{ .reg .b32 v, t; cvt.rn.bf16x2.f32 v, %2, %1; mul.rn.bf16x2 t, v, v; fma.rn.bf16x2 t, t, %3, %4; mul.rn.bf16x2 t, t, v; tanh.approx.bf16x2 t, t; fma.rn.bf16x2 %0, v, t, v; }"
      : "=r"(r) : "f"(lo), "f"(hi), "r"(0x40124012u), "r"(0x404c404cu));
  return r;
}
__device__ __forceinline__ float sqrt_fast(float x) { float r; asm("sqrt.approx.ftz.f32 %0, %1;" : "=f"(r) : "f"(x)); return r; }
__device__ __forceinline__ float rcp_fast(float x) { float r; asm("rcp.approx.ftz.f32 %0, %1;" : "=f"(r) : "f"(x)); return r; }
__device__ __forceinline__ float tanhf_fast(float x) { float r; asm("tanh.approx.f32 %0, %1;" : "=f"(r) : "f"(x)); return r; }
__device__ __forceinline__ uint2 ldr64(const void* p) { uint2 v; asm volatile("ld.relaxed.gpu.global.v2.b32 {%0,%1}, [%2];" : "=r"(v.x), "=r"(v.y) : "l"(p) : "memory"); return v; }
constexpr int SPIN = 1 << 17;
__device__ __forceinline__ bool retry(uint32_t bad, int& n) { if (bad == 0u) return false; __nanosleep(100); return ++n < SPIN; }
__device__ __forceinline__ void st_b128(int pr, void* p, uint32_t a, uint32_t b, uint32_t c, uint32_t d) {
  asm volatile("{ .reg .pred p; setp.ne.b32 p, %5, 0; @p st.relaxed.gpu.global.v4.b32 [%0], {%1,%2,%3,%4}; }"
               ::"l"(p), "r"(a), "r"(b), "r"(c), "r"(d), "r"(pr) : "memory");
}
__device__ __forceinline__ void st_b64(int pr, void* p, uint32_t a, uint32_t b) {
  asm volatile("{ .reg .pred p; setp.ne.b32 p, %3, 0; @p st.relaxed.gpu.global.v2.b32 [%0], {%1,%2}; }" ::"l"(p), "r"(a), "r"(b), "r"(pr) : "memory");
}
__device__ __forceinline__ void ld_rec(uint32_t* r, const unsigned char* p, const unsigned char* p2) {
  asm volatile("ld.relaxed.gpu.global.v4.b32 {%0,%1,%2,%3}, [%16];\n ld.relaxed.gpu.global.v4.b32 {%4,%5,%6,%7}, [%16+4096];\n"
               "ld.relaxed.gpu.global.v4.b32 {%8,%9,%10,%11}, [%17];\n ld.relaxed.gpu.global.v4.b32 {%12,%13,%14,%15}, [%17+4096];"
               : "=r"(r[0]), "=r"(r[1]), "=r"(r[2]), "=r"(r[3]), "=r"(r[4]), "=r"(r[5]), "=r"(r[6]), "=r"(r[7]), "=r"(r[8]), "=r"(r[9]), "=r"(r[10]),
                 "=r"(r[11]), "=r"(r[12]), "=r"(r[13]), "=r"(r[14]), "=r"(r[15]) : "l"(p), "l"(p2) : "memory");
}
__device__ __forceinline__ uint32_t rec_bad(const uint32_t* r, uint32_t tag, uint32_t m2) { return (((r[3] ^ tag) | (r[7] ^ tag)) & 0x00010001u) | (((r[11] ^ tag) | (r[15] ^ tag)) & m2); }
__device__ __forceinline__ void mbar_arrive(uint32_t bar) { asm volatile("mbarrier.arrive.shared::cta.b64 _, [%0];" ::"r"(bar) : "memory"); }
__device__ __forceinline__ uint32_t ldg16(const void* p) { uint32_t v; asm volatile("ld.global.nc.u16 %0, [%1];" : "=r"(v) : "l"(p)); return v; }
__device__ __forceinline__ uint4 ldg128(const void* p) { uint4 v; asm volatile("ld.global.nc.v4.b32 {%0,%1,%2,%3}, [%4];" : "=r"(v.x), "=r"(v.y), "=r"(v.z), "=r"(v.w) : "l"(p)); return v; }
__device__ __forceinline__ void sts16(uint32_t addr, uint32_t v) { asm volatile("st.shared.b16 [%0], %1;" ::"r"(addr), "h"((unsigned short)v) : "memory"); }
__device__ __forceinline__ uint32_t keep(uint32_t v) { asm volatile("{ .reg .pred p; .reg .b32 z; mov.u32 z, %%ctaid.y; setp.ne.b32 p, z, 0; @p ld.shared.b32 %0, [%0]; }" : "+r"(v)); return v; }
__device__ __forceinline__ void sts32(uint32_t addr, uint32_t v) { asm volatile("st.shared.b32 [%0], %1;" ::"r"(addr), "r"(v) : "memory"); }
__device__ __forceinline__ uint64_t desc64(uint32_t lo, uint32_t hi) { uint64_t d; asm("mov.b64 %0, {%1,%2};" : "=l"(d) : "r"(lo), "r"(hi)); return d; }
struct cf { float r, i; };
__device__ __forceinline__ cf cmul(cf a, cf b) { return {fmaf(a.r, b.r, -(a.i * b.i)), fmaf(a.r, b.i, a.i * b.r)}; }
__device__ __forceinline__ cf csq(cf a) { return {fmaf(a.r, a.r, -(a.i * a.i)), 2.f * (a.r * a.i)}; }
__device__ __forceinline__ cf cexp_p(float zr2, float zi, float p) {
  float m = ex2f(zr2 * p), a = zi * p;
  return {m * __cosf(a), m * __sinf(a)};
}

__device__ __forceinline__ void wgmma_rs_n192(float (&d)[112], uint32_t a0, uint32_t a1, uint32_t a2, uint32_t a3, uint64_t db, int scale_d) {
  asm volatile("{ .reg .pred p; setp.ne.b32 p, %101, 0;\n"
    "wgmma.mma_async.sync.aligned.m64n192k16.f32.bf16.bf16 {%0,%1,%2,%3,%4,%5,%6,%7,%8,%9,%10,%11,%12,%13,%14,%15,%16,%17,%18,%19,%20,%21,%22,%23,%24,%25,%26,%27,%28,%29,%30,%31,%32,%33,%34,%35,%36,%37,%38,%39,%40,%41,%42,%43,%44,%45,%46,%47,%48,%49,%50,%51,%52,%53,%54,%55,%56,%57,%58,%59,%60,%61,%62,%63,%64,%65,%66,%67,%68,%69,%70,%71,%72,%73,%74,%75,%76,%77,%78,%79,%80,%81,%82,%83,%84,%85,%86,%87,%88,%89,%90,%91,%92,%93,%94,%95}, {%96,%97,%98,%99}, %100, p, 1, 1, 1; }"
    : "+f"(d[0]), "+f"(d[1]), "+f"(d[2]), "+f"(d[3]), "+f"(d[4]), "+f"(d[5]), "+f"(d[6]), "+f"(d[7]),
      "+f"(d[8]), "+f"(d[9]), "+f"(d[10]), "+f"(d[11]), "+f"(d[12]), "+f"(d[13]), "+f"(d[14]), "+f"(d[15]),
      "+f"(d[16]), "+f"(d[17]), "+f"(d[18]), "+f"(d[19]), "+f"(d[20]), "+f"(d[21]), "+f"(d[22]), "+f"(d[23]),
      "+f"(d[24]), "+f"(d[25]), "+f"(d[26]), "+f"(d[27]), "+f"(d[28]), "+f"(d[29]), "+f"(d[30]), "+f"(d[31]),
      "+f"(d[32]), "+f"(d[33]), "+f"(d[34]), "+f"(d[35]), "+f"(d[36]), "+f"(d[37]), "+f"(d[38]), "+f"(d[39]),
      "+f"(d[40]), "+f"(d[41]), "+f"(d[42]), "+f"(d[43]), "+f"(d[44]), "+f"(d[45]), "+f"(d[46]), "+f"(d[47]),
      "+f"(d[48]), "+f"(d[49]), "+f"(d[50]), "+f"(d[51]), "+f"(d[52]), "+f"(d[53]), "+f"(d[54]), "+f"(d[55]),
      "+f"(d[56]), "+f"(d[57]), "+f"(d[58]), "+f"(d[59]), "+f"(d[60]), "+f"(d[61]), "+f"(d[62]), "+f"(d[63]),
      "+f"(d[64]), "+f"(d[65]), "+f"(d[66]), "+f"(d[67]), "+f"(d[68]), "+f"(d[69]), "+f"(d[70]), "+f"(d[71]),
      "+f"(d[72]), "+f"(d[73]), "+f"(d[74]), "+f"(d[75]), "+f"(d[76]), "+f"(d[77]), "+f"(d[78]), "+f"(d[79]),
      "+f"(d[80]), "+f"(d[81]), "+f"(d[82]), "+f"(d[83]), "+f"(d[84]), "+f"(d[85]), "+f"(d[86]), "+f"(d[87]),
      "+f"(d[88]), "+f"(d[89]), "+f"(d[90]), "+f"(d[91]), "+f"(d[92]), "+f"(d[93]), "+f"(d[94]), "+f"(d[95])
    : "r"(a0), "r"(a1), "r"(a2), "r"(a3), "l"(db), "r"(scale_d));
}

__device__ __forceinline__ void wgmma_rs_n32(float (&d)[112], uint32_t a0, uint32_t a1, uint32_t a2, uint32_t a3, uint64_t db, int scale_d) {
  asm volatile("{ .reg .pred p; setp.ne.b32 p, %21, 0;\n"
    "wgmma.mma_async.sync.aligned.m64n32k16.f32.bf16.bf16 {%0,%1,%2,%3,%4,%5,%6,%7,%8,%9,%10,%11,%12,%13,%14,%15}, {%16,%17,%18,%19}, %20, p, 1, 1, 1; }"
    : "+f"(d[96]), "+f"(d[97]), "+f"(d[98]), "+f"(d[99]), "+f"(d[100]), "+f"(d[101]), "+f"(d[102]), "+f"(d[103]),
      "+f"(d[104]), "+f"(d[105]), "+f"(d[106]), "+f"(d[107]), "+f"(d[108]), "+f"(d[109]), "+f"(d[110]), "+f"(d[111])
    : "r"(a0), "r"(a1), "r"(a2), "r"(a3), "l"(db), "r"(scale_d));
}

#define R32 "%0,%1,%2,%3,%4,%5,%6,%7,%8,%9,%10,%11,%12,%13,%14,%15"
#define R64 "%0,%1,%2,%3,%4,%5,%6,%7,%8,%9,%10,%11,%12,%13,%14,%15,%16,%17,%18,%19,%20,%21,%22,%23,%24,%25,%26,%27,%28,%29,%30,%31"
__device__ __forceinline__ void gemm2_pass(float (&d)[32], const uint32_t (&h)[56], const uint32_t (&hp)[52], uint64_t d0a, uint64_t d0b, uint64_t d1a, uint64_t d1b, uint64_t dl, int half, int next_bar) {
  asm volatile("{ .reg .pred p, q, r; setp.ne.b32 r, %146, 0; .reg .b64 t; .reg .b32 z; mov.u32 z, %%ctaid.y; setp.ne.b32 q, z, 0; setp.ne.b32 p, %145, 0; @p bra.uni G2HALF;\n"
    "wgmma.fence.sync.aligned;\n"
    "add.s64 t, %140, 0; wgmma.mma_async.sync.aligned.m64n64k16.f32.bf16.bf16 {" R64 "}, {%32,%33,%34,%35}, t, q, 1, 1, 1;\n"
    "add.s64 t, %140, 128; wgmma.mma_async.sync.aligned.m64n64k16.f32.bf16.bf16 {" R64 "}, {%36,%37,%38,%39}, t, 1, 1, 1, 1;\n"
    "add.s64 t, %140, 256; wgmma.mma_async.sync.aligned.m64n64k16.f32.bf16.bf16 {" R64 "}, {%40,%41,%42,%43}, t, 1, 1, 1, 1;\n"
    "add.s64 t, %140, 384; wgmma.mma_async.sync.aligned.m64n64k16.f32.bf16.bf16 {" R64 "}, {%44,%45,%46,%47}, t, 1, 1, 1, 1;\n"
    "add.s64 t, %140, 512; wgmma.mma_async.sync.aligned.m64n64k16.f32.bf16.bf16 {" R64 "}, {%48,%49,%50,%51}, t, 1, 1, 1, 1;\n"
    "add.s64 t, %140, 640; wgmma.mma_async.sync.aligned.m64n64k16.f32.bf16.bf16 {" R64 "}, {%52,%53,%54,%55}, t, 1, 1, 1, 1;\n"
    "add.s64 t, %140, 768; wgmma.mma_async.sync.aligned.m64n64k16.f32.bf16.bf16 {" R64 "}, {%56,%57,%58,%59}, t, 1, 1, 1, 1;\n"
    "add.s64 t, %140, 896; wgmma.mma_async.sync.aligned.m64n64k16.f32.bf16.bf16 {" R64 "}, {%60,%61,%62,%63}, t, 1, 1, 1, 1;\n"
    "add.s64 t, %140, 1024; wgmma.mma_async.sync.aligned.m64n64k16.f32.bf16.bf16 {" R64 "}, {%64,%65,%66,%67}, t, 1, 1, 1, 1;\n"
    "add.s64 t, %140, 1152; wgmma.mma_async.sync.aligned.m64n64k16.f32.bf16.bf16 {" R64 "}, {%68,%69,%70,%71}, t, 1, 1, 1, 1;\n"
    "add.s64 t, %140, 1280; wgmma.mma_async.sync.aligned.m64n64k16.f32.bf16.bf16 {" R64 "}, {%72,%73,%74,%75}, t, 1, 1, 1, 1;\n"
    "add.s64 t, %140, 1408; wgmma.mma_async.sync.aligned.m64n64k16.f32.bf16.bf16 {" R64 "}, {%76,%77,%78,%79}, t, 1, 1, 1, 1;\n"
    "add.s64 t, %141, 0; wgmma.mma_async.sync.aligned.m64n64k16.f32.bf16.bf16 {" R64 "}, {%80,%81,%82,%83}, t, 1, 1, 1, 1;\n"
    "add.s64 t, %141, 128; wgmma.mma_async.sync.aligned.m64n64k16.f32.bf16.bf16 {" R64 "}, {%84,%85,%86,%87}, t, 1, 1, 1, 1;\n"
    "add.s64 t, %142, 0; wgmma.mma_async.sync.aligned.m64n64k16.f32.bf16.bf16 {" R64 "}, {%88,%89,%90,%91}, t, 1, 1, 1, 1;\n"
    "add.s64 t, %142, 128; wgmma.mma_async.sync.aligned.m64n64k16.f32.bf16.bf16 {" R64 "}, {%92,%93,%94,%95}, t, 1, 1, 1, 1;\n"
    "add.s64 t, %142, 256; wgmma.mma_async.sync.aligned.m64n64k16.f32.bf16.bf16 {" R64 "}, {%96,%97,%98,%99}, t, 1, 1, 1, 1;\n"
    "add.s64 t, %142, 384; wgmma.mma_async.sync.aligned.m64n64k16.f32.bf16.bf16 {" R64 "}, {%100,%101,%102,%103}, t, 1, 1, 1, 1;\n"
    "add.s64 t, %142, 512; wgmma.mma_async.sync.aligned.m64n64k16.f32.bf16.bf16 {" R64 "}, {%104,%105,%106,%107}, t, 1, 1, 1, 1;\n"
    "add.s64 t, %142, 640; wgmma.mma_async.sync.aligned.m64n64k16.f32.bf16.bf16 {" R64 "}, {%108,%109,%110,%111}, t, 1, 1, 1, 1;\n"
    "add.s64 t, %142, 768; wgmma.mma_async.sync.aligned.m64n64k16.f32.bf16.bf16 {" R64 "}, {%112,%113,%114,%115}, t, 1, 1, 1, 1;\n"
    "add.s64 t, %142, 896; wgmma.mma_async.sync.aligned.m64n64k16.f32.bf16.bf16 {" R64 "}, {%116,%117,%118,%119}, t, 1, 1, 1, 1;\n"
    "add.s64 t, %142, 1024; wgmma.mma_async.sync.aligned.m64n64k16.f32.bf16.bf16 {" R64 "}, {%120,%121,%122,%123}, t, 1, 1, 1, 1;\n"
    "add.s64 t, %142, 1152; wgmma.mma_async.sync.aligned.m64n64k16.f32.bf16.bf16 {" R64 "}, {%124,%125,%126,%127}, t, 1, 1, 1, 1;\n"
    "add.s64 t, %142, 1280; wgmma.mma_async.sync.aligned.m64n64k16.f32.bf16.bf16 {" R64 "}, {%128,%129,%130,%131}, t, 1, 1, 1, 1;\n"
    "@r bar.arrive %146, 256;\n"
    "add.s64 t, %142, 1408; wgmma.mma_async.sync.aligned.m64n64k16.f32.bf16.bf16 {" R64 "}, {%132,%133,%134,%135}, t, 1, 1, 1, 1;\n"
    "add.s64 t, %143, 0; wgmma.mma_async.sync.aligned.m64n64k16.f32.bf16.bf16 {" R64 "}, {%136,%137,%138,%139}, t, 1, 1, 1, 1;\n"
    "add.s64 t, %143, 128; wgmma.mma_async.sync.aligned.m64n64k16.f32.bf16.bf16 {" R64 "}, %144, t, 1, 1, 1, 0, 1;\n"
    "wgmma.commit_group.sync.aligned;\n"
    "bra.uni G2END;\n G2HALF:\n"
    "wgmma.fence.sync.aligned;\n"
    "add.s64 t, %140, 0; wgmma.mma_async.sync.aligned.m64n32k16.f32.bf16.bf16 {" R32 "}, {%32,%33,%34,%35}, t, q, 1, 1, 1;\n"
    "add.s64 t, %140, 128; wgmma.mma_async.sync.aligned.m64n32k16.f32.bf16.bf16 {" R32 "}, {%36,%37,%38,%39}, t, 1, 1, 1, 1;\n"
    "add.s64 t, %140, 256; wgmma.mma_async.sync.aligned.m64n32k16.f32.bf16.bf16 {" R32 "}, {%40,%41,%42,%43}, t, 1, 1, 1, 1;\n"
    "add.s64 t, %140, 384; wgmma.mma_async.sync.aligned.m64n32k16.f32.bf16.bf16 {" R32 "}, {%44,%45,%46,%47}, t, 1, 1, 1, 1;\n"
    "add.s64 t, %140, 512; wgmma.mma_async.sync.aligned.m64n32k16.f32.bf16.bf16 {" R32 "}, {%48,%49,%50,%51}, t, 1, 1, 1, 1;\n"
    "add.s64 t, %140, 640; wgmma.mma_async.sync.aligned.m64n32k16.f32.bf16.bf16 {" R32 "}, {%52,%53,%54,%55}, t, 1, 1, 1, 1;\n"
    "add.s64 t, %140, 768; wgmma.mma_async.sync.aligned.m64n32k16.f32.bf16.bf16 {" R32 "}, {%56,%57,%58,%59}, t, 1, 1, 1, 1;\n"
    "add.s64 t, %140, 896; wgmma.mma_async.sync.aligned.m64n32k16.f32.bf16.bf16 {" R32 "}, {%60,%61,%62,%63}, t, 1, 1, 1, 1;\n"
    "add.s64 t, %140, 1024; wgmma.mma_async.sync.aligned.m64n32k16.f32.bf16.bf16 {" R32 "}, {%64,%65,%66,%67}, t, 1, 1, 1, 1;\n"
    "add.s64 t, %140, 1152; wgmma.mma_async.sync.aligned.m64n32k16.f32.bf16.bf16 {" R32 "}, {%68,%69,%70,%71}, t, 1, 1, 1, 1;\n"
    "add.s64 t, %140, 1280; wgmma.mma_async.sync.aligned.m64n32k16.f32.bf16.bf16 {" R32 "}, {%72,%73,%74,%75}, t, 1, 1, 1, 1;\n"
    "add.s64 t, %140, 1408; wgmma.mma_async.sync.aligned.m64n32k16.f32.bf16.bf16 {" R32 "}, {%76,%77,%78,%79}, t, 1, 1, 1, 1;\n"
    "add.s64 t, %141, 0; wgmma.mma_async.sync.aligned.m64n32k16.f32.bf16.bf16 {" R32 "}, {%80,%81,%82,%83}, t, 1, 1, 1, 1;\n"
    "add.s64 t, %141, 128; wgmma.mma_async.sync.aligned.m64n32k16.f32.bf16.bf16 {" R32 "}, {%84,%85,%86,%87}, t, 1, 1, 1, 1;\n"
    "add.s64 t, %142, 0; wgmma.mma_async.sync.aligned.m64n32k16.f32.bf16.bf16 {" R32 "}, {%88,%89,%90,%91}, t, 1, 1, 1, 1;\n"
    "add.s64 t, %142, 128; wgmma.mma_async.sync.aligned.m64n32k16.f32.bf16.bf16 {" R32 "}, {%92,%93,%94,%95}, t, 1, 1, 1, 1;\n"
    "add.s64 t, %142, 256; wgmma.mma_async.sync.aligned.m64n32k16.f32.bf16.bf16 {" R32 "}, {%96,%97,%98,%99}, t, 1, 1, 1, 1;\n"
    "add.s64 t, %142, 384; wgmma.mma_async.sync.aligned.m64n32k16.f32.bf16.bf16 {" R32 "}, {%100,%101,%102,%103}, t, 1, 1, 1, 1;\n"
    "add.s64 t, %142, 512; wgmma.mma_async.sync.aligned.m64n32k16.f32.bf16.bf16 {" R32 "}, {%104,%105,%106,%107}, t, 1, 1, 1, 1;\n"
    "add.s64 t, %142, 640; wgmma.mma_async.sync.aligned.m64n32k16.f32.bf16.bf16 {" R32 "}, {%108,%109,%110,%111}, t, 1, 1, 1, 1;\n"
    "add.s64 t, %142, 768; wgmma.mma_async.sync.aligned.m64n32k16.f32.bf16.bf16 {" R32 "}, {%112,%113,%114,%115}, t, 1, 1, 1, 1;\n"
    "add.s64 t, %142, 896; wgmma.mma_async.sync.aligned.m64n32k16.f32.bf16.bf16 {" R32 "}, {%116,%117,%118,%119}, t, 1, 1, 1, 1;\n"
    "@r bar.arrive %146, 256;\n"
    "add.s64 t, %142, 1024; wgmma.mma_async.sync.aligned.m64n32k16.f32.bf16.bf16 {" R32 "}, {%120,%121,%122,%123}, t, 1, 1, 1, 1;\n"
    "add.s64 t, %142, 1152; wgmma.mma_async.sync.aligned.m64n32k16.f32.bf16.bf16 {" R32 "}, {%124,%125,%126,%127}, t, 1, 1, 1, 1;\n"
    "add.s64 t, %142, 1280; wgmma.mma_async.sync.aligned.m64n32k16.f32.bf16.bf16 {" R32 "}, {%128,%129,%130,%131}, t, 1, 1, 1, 1;\n"
    "add.s64 t, %142, 1408; wgmma.mma_async.sync.aligned.m64n32k16.f32.bf16.bf16 {" R32 "}, {%132,%133,%134,%135}, t, 1, 1, 1, 1;\n"
    "add.s64 t, %143, 0; wgmma.mma_async.sync.aligned.m64n32k16.f32.bf16.bf16 {" R32 "}, {%136,%137,%138,%139}, t, 1, 1, 1, 1;\n"
    "add.s64 t, %143, 128; wgmma.mma_async.sync.aligned.m64n32k16.f32.bf16.bf16 {" R32 "}, %144, t, 1, 1, 1, 0, 1;\n"
    "wgmma.commit_group.sync.aligned;\n"
    "G2END:\n }"
    : "+f"(d[0]), "+f"(d[1]), "+f"(d[2]), "+f"(d[3]), "+f"(d[4]), "+f"(d[5]), "+f"(d[6]), "+f"(d[7]),
      "+f"(d[8]), "+f"(d[9]), "+f"(d[10]), "+f"(d[11]), "+f"(d[12]), "+f"(d[13]), "+f"(d[14]), "+f"(d[15]),
      "+f"(d[16]), "+f"(d[17]), "+f"(d[18]), "+f"(d[19]), "+f"(d[20]), "+f"(d[21]), "+f"(d[22]), "+f"(d[23]),
      "+f"(d[24]), "+f"(d[25]), "+f"(d[26]), "+f"(d[27]), "+f"(d[28]), "+f"(d[29]), "+f"(d[30]), "+f"(d[31])
    : "r"(h[0]), "r"(h[1]), "r"(h[2]), "r"(h[3]), "r"(h[4]), "r"(h[5]), "r"(h[6]), "r"(h[7]),
      "r"(h[8]), "r"(h[9]), "r"(h[10]), "r"(h[11]), "r"(h[12]), "r"(h[13]), "r"(h[14]), "r"(h[15]),
      "r"(h[16]), "r"(h[17]), "r"(h[18]), "r"(h[19]), "r"(h[20]), "r"(h[21]), "r"(h[22]), "r"(h[23]),
      "r"(h[24]), "r"(h[25]), "r"(h[26]), "r"(h[27]), "r"(h[28]), "r"(h[29]), "r"(h[30]), "r"(h[31]),
      "r"(h[32]), "r"(h[33]), "r"(h[34]), "r"(h[35]), "r"(h[36]), "r"(h[37]), "r"(h[38]), "r"(h[39]),
      "r"(h[40]), "r"(h[41]), "r"(h[42]), "r"(h[43]), "r"(h[44]), "r"(h[45]), "r"(h[46]), "r"(h[47]),
      "r"(h[48]), "r"(h[49]), "r"(h[50]), "r"(h[51]), "r"(h[52]), "r"(h[53]), "r"(h[54]), "r"(h[55]),
      "r"(hp[0]), "r"(hp[1]), "r"(hp[2]), "r"(hp[3]), "r"(hp[4]), "r"(hp[5]), "r"(hp[6]), "r"(hp[7]),
      "r"(hp[8]), "r"(hp[9]), "r"(hp[10]), "r"(hp[11]), "r"(hp[12]), "r"(hp[13]), "r"(hp[14]), "r"(hp[15]),
      "r"(hp[16]), "r"(hp[17]), "r"(hp[18]), "r"(hp[19]), "r"(hp[20]), "r"(hp[21]), "r"(hp[22]), "r"(hp[23]),
      "r"(hp[24]), "r"(hp[25]), "r"(hp[26]), "r"(hp[27]), "r"(hp[28]), "r"(hp[29]), "r"(hp[30]), "r"(hp[31]),
      "r"(hp[32]), "r"(hp[33]), "r"(hp[34]), "r"(hp[35]), "r"(hp[36]), "r"(hp[37]), "r"(hp[38]), "r"(hp[39]),
      "r"(hp[40]), "r"(hp[41]), "r"(hp[42]), "r"(hp[43]), "r"(hp[44]), "r"(hp[45]), "r"(hp[46]), "r"(hp[47]),
      "r"(hp[48]), "r"(hp[49]), "r"(hp[50]), "r"(hp[51]),
      "l"(d0a), "l"(d0b), "l"(d1a), "l"(d1b), "l"(dl), "r"(half), "r"(next_bar) : "memory");
}

struct Maps { CUtensorMap w1, x, w1a, w1h, w2a, y, xt, out[3]; };
struct Params {
  const __nv_bfloat16 *logA, *Aim, *Cre, *Cim, *logdt, *Dskip, *x, *b1, *w2, *b2;
};

__device__ __forceinline__ uint32_t w2_slot(int T) { return (uint32_t)(0x684ca0841c00684cull >> (8 * T) & 0xffu) << 10; }
static_assert(OFF_W + W_STAGE == 0x4c << 10 && OFF_W + 2 * W_STAGE == 0x68 << 10 && W_STAGE == 0x1c << 10 && OFF_S == 0x84 << 10, "slots");
__device__ __forceinline__ int chunk_col(int i, int c) { return c == 3 ? 192 + 32 * i : 256 * i + 64 * c; }
__device__ __forceinline__ void issue_w2(int T, uint32_t sb, int fs, const Maps& M) {
  uint32_t bar = sb + MB_W2 + T * 8;
  const int c = ((fs >> 1) + 1 + (T >> 1)) & 3;
  mbar_expect(bar, W_STAGE);
  tma2d(sb + w2_slot(T), &M.w2a, c == 3 ? 192 : chunk_col(fs & 1, c), 224 * (fs ^ (T & 1)), bar);
}

__device__ __forceinline__ uint32_t hfma2n(uint32_t a, uint32_t b, uint32_t c) { uint32_t r; asm("{ .reg .b32 t; neg.f16x2 t, %3; fma.rn.f16x2 %0, %1, %2, t; }" : "=r"(r) : "r"(a), "r"(b), "r"(c)); return r; }
__device__ __forceinline__ void kgen_batch(float (&acc)[5][4], float la, float ai, float cr, float ci, float dt, uint32_t re, uint32_t ua, uint32_t aA, uint32_t aB, uint32_t aC, uint32_t aU) {
  float ar = bf_round(ex2f(la * 1.4426950408889634f));
  float zr2 = -(ar * dt) * 1.4426950408889634f, zi = ai * dt;
  cf w1 = cexp_p(zr2, zi, 1.f), v1 = cexp_p(zr2, -zi, 8.f), w256 = cexp_p(zr2, zi, 256.f);
  const uint32_t im = re + 2560;
  cf v2 = csq(v1), v3 = cmul(v2, v1), v4 = csq(v2), v5 = cmul(v4, v1), v6 = csq(v3), v7 = cmul(v4, v3), u1 = csq(v4), u2 = csq(u1);
  uint32_t jr[4] = {pack_h2(1.f, v1.r), pack_h2(v2.r, v3.r), pack_h2(v4.r, v5.r), pack_h2(v6.r, v7.r)};
  uint32_t ji[4] = {pack_h2(0.f, v1.i), pack_h2(v2.i, v3.i), pack_h2(v4.i, v5.i), pack_h2(v6.i, v7.i)};
  sts128(re, jr[0], jr[1], jr[2], jr[3]);
  sts128(im, ji[0], ji[1], ji[2], ji[3]);
  const uint32_t wr = pack_h2(u1.r, u1.r), wi = pack_h2(u1.i, u1.i), pu = pack_h2(u2.r, u2.i);
  sts128(re + 16, hfma2n(jr[0], wr, hmul2(ji[0], wi)), hfma2n(jr[1], wr, hmul2(ji[1], wi)), hfma2n(jr[2], wr, hmul2(ji[2], wi)), hfma2n(jr[3], wr, hmul2(ji[3], wi)));
  sts128(im + 16, hfma2(jr[0], wi, hmul2(ji[0], wr)), hfma2(jr[1], wi, hmul2(ji[1], wr)), hfma2(jr[2], wi, hmul2(ji[2], wr)), hfma2(jr[3], wi, hmul2(ji[3], wr)));
  sts16(ua, pu); sts16(ua + 64, pu >> 16);
  cf c[8];
  c[0] = cmul({cr, ci}, w1);
#pragma unroll
  for (int k = 1; k < 8; k++) c[k] = cmul(c[k - 1], w1);
  sts128(re + 32, pack_h2(c[0].r, c[1].r), pack_h2(c[2].r, c[3].r), pack_h2(c[4].r, c[5].r), pack_h2(c[6].r, c[7].r));
  sts128(im + 32, pack_h2(c[0].i, c[1].i), pack_h2(c[2].i, c[3].i), pack_h2(c[4].i, c[5].i), pack_h2(c[6].i, c[7].i));
  cf a258 = cmul(c[1], w256), a260 = cmul(c[3], w256), a262 = cmul(c[5], w256), a264 = cmul(c[7], w256);
  cf a516 = cmul(a260, w256), a520 = cmul(a264, w256), a772 = cmul(a516, w256), a776 = cmul(a520, w256);
  sts128(re + 48, pack_h2(a258.r, a260.r), pack_h2(a262.r, a264.r), pack_h2(a516.r, a772.r), pack_h2(a520.r, a776.r));
  sts128(im + 48, pack_h2(a258.i, a260.i), pack_h2(a262.i, a264.i), pack_h2(a516.i, a772.i), pack_h2(a520.i, a776.i));
  const cf w128 = {u2.r, -u2.i};
  cf b0 = cmul(a776, w256), b2 = cmul(b0, w256), b4 = cmul(b2, w256), b6 = cmul(b4, w256);
  cf b1 = cmul(b0, w128), b3 = cmul(b2, w128), b5 = cmul(b4, w128), b7 = cmul(b6, w128);
  sts128(re + 64, pack_h2(b0.r, b4.r), pack_h2(b1.r, b5.r), pack_h2(b2.r, b6.r), pack_h2(b3.r, b7.r));
  sts128(im + 64, pack_h2(b0.i, b4.i), pack_h2(b1.i, b5.i), pack_h2(b2.i, b6.i), pack_h2(b3.i, b7.i));
  __syncwarp();
  uint32_t ur[4], ui[4];
  ldsm4(ur[0], ur[1], ur[2], ur[3], aU);
  ldsm4(ui[0], ui[1], ui[2], ui[3], aU + 64);
#pragma unroll
  for (int kp = 0; kp < 2; kp++) {
    uint32_t c4[4];
    ldsm4t(c4[0], c4[1], c4[2], c4[3], aC + kp * 1280);
#pragma unroll
    for (int kk = 0; kk < 2; kk++) {
      const int ks = 2 * kp + kk;
      uint32_t a[4], b[4];
      ldsm4t(a[0], a[1], a[2], a[3], aA + ks * 640);
      ldsm4t(b[0], b[1], b[2], b[3], aB + ks * 640);
      const uint32_t r2 = hfma2n(a[0], ur[ks], hmul2(a[2], ui[ks])), r3 = hfma2n(a[1], ur[ks], hmul2(a[3], ui[ks]));
      const uint32_t i2 = hfma2(a[0], ui[ks], hmul2(a[2], ur[ks])), i3 = hfma2(a[1], ui[ks], hmul2(a[3], ur[ks]));
      hmma(acc[0][0], acc[0][1], acc[0][2], acc[0][3], a[0], a[1], a[2], a[3], b[0], b[1]);
      hmma(acc[1][0], acc[1][1], acc[1][2], acc[1][3], a[0], a[1], a[2], a[3], b[2], b[3]);
      hmma(acc[2][0], acc[2][1], acc[2][2], acc[2][3], a[0], a[1], a[2], a[3], c4[2 * kk], c4[2 * kk + 1]);
      hmma(acc[3][0], acc[3][1], acc[3][2], acc[3][3], r2, r3, i2, i3, b[0], b[1]);
      hmma(acc[4][0], acc[4][1], acc[4][2], acc[4][3], r2, r3, i2, i3, b[2], b[3]);
    }
  }
  __syncwarp();
}

template <int D0, int ND>
__device__ __forceinline__ void conv_A(float (&acc)[16][4], uint32_t ta, uint32_t lb, uint32_t z, uint32_t& tok) {
  ta += tok; lb += tok;
  uint32_t a[ND][4];
#pragma unroll
  for (int d = 0; d < ND; d++) { lds64(a[d][0], a[d][1], ta + 64 * (D0 + d)); a[d][2] = lds32(ta + 64 * (D0 + d) - 4); a[d][3] = a[d][0] ^ z; }
  constexpr int NP = (32 - D0) / 2, H = (NP + 1) / 2;
#pragma unroll
  for (int pp = 0; pp < H; pp++) {
    uint32_t b[2][4];
#pragma unroll
    for (int u = 0; u < 2; u++) { int p = pp + u * H; if (p < NP) ldsm4(b[u][0], b[u][1], b[u][2], b[u][3], lb + (2 * p - 1) * 16); }
#pragma unroll
    for (int d = 0; d < ND; d++)
#pragma unroll
      for (int u = 0; u < 2; u++) {
        int p = pp + u * H, dl = D0 + d, odd = dl & 1;
        int s = odd ? 2 * p - 1 : 2 * p, al = (s + dl) / 2;
        if (p < NP && al <= 15)
          hmma(acc[al][0], acc[al][1], acc[al][2], acc[al][3], a[d][0], a[d][1], a[d][2], a[d][3], b[u][odd ? 0 : 2], b[u][odd ? 1 : 3]);
      }
    if (pp == H - 4) tok = __float_as_uint(acc[pp + D0 / 2][0]) & z;
  }
}
template <int D0, int ND>
__device__ __forceinline__ void conv_B(float (&acc)[16][4], uint32_t tb, uint32_t lb, uint32_t z, uint32_t& tok) {
  tb += tok; lb += tok;
  uint32_t f[ND][4];
#pragma unroll
  for (int d = 0; d < ND; d++) {
    uint32_t t = tb + 64 * (D0 + d);
    f[d][0] = lds32(t); f[d][1] = lds32(t + 32); f[d][2] = d ? f[d - 1][1] ^ z : lds32(t - 32); f[d][3] = f[d][0] ^ z;
  }
  constexpr int NP = (16 - D0) / 2;
#pragma unroll
  for (int p = 0; p < NP; p++) {
    uint32_t b[4];
    ldsm4(b[0], b[1], b[2], b[3], lb + p * 64);
#pragma unroll
    for (int u = 0; u < 2; u++)
#pragma unroll
      for (int d = 0; d < ND; d++) {
        int al = 2 * p + u + D0 + d;
        if (al <= 15)
          hmma(acc[al][0], acc[al][2], acc[al][1], acc[al][3], f[d][0], f[d][1], f[d][2], f[d][3], b[2 * u], b[2 * u + 1]);
      }
    if (p == (D0 == 8 ? 0 : 1)) tok = __float_as_uint(acc[2 * p + D0][0]) & z;
  }
}

__global__ void __cluster_dims__(2, 1, 1) __launch_bounds__(NTHR, 1)
fused_kernel(const Params P, const __grid_constant__ Maps M) {
  const int tid = threadIdx.x;
  const int cta = ((blockIdx.x >> 1) & 15) * 8 + ((blockIdx.x >> 5) << 1) + (blockIdx.x & 1);
  const int n0 = min(cta, 111) * (4 * NS) + (tid & 127) * 8;
  const uint4 vla = ldg128(P.logA + n0), vai = ldg128(P.Aim + n0), vcr = ldg128(P.Cre + n0), vci = ldg128(P.Cim + n0);
  const uint32_t wdt = ldg16(P.logdt + (n0 >> 8)), wdk = ldg16(P.Dskip + (n0 >> 8));
  extern __shared__ unsigned char smem_raw[];
  const uint32_t sb = (smem_u32(smem_raw) + 1023u) & ~1023u;
  unsigned char* sm = smem_raw + (sb - smem_u32(smem_raw));
  const int lane = tid & 31;
  const int warp = __shfl_sync(0xffffffffu, tid >> 5, 0);
  const int rb = cta >> 3, fs = cta & 7;
  const bool has_ch = cta < 112;
  const int g = lane >> 2, q = lane & 3;
  const int wg = warp >> 2, v = warp & 3;
  const int d = cta * 4 + v;
  const uint32_t bs = sb + OFF_S + v * S_BLK;
  const int oc0 = chunk_col(fs & 1, fs >> 1);

  if (lane == 0) {
    mbar_init(sb + M_BAR + warp * 8, warp < 7 ? 3 : 1);
    mbar_init(sb + M_BAR + 96 + warp * 8, wg == 1 ? 8 : 1);
    if (warp == 8) mbar_expect(sb + MB_H, 2 * W_STAGE);
    if (warp < 7) mbar_init(sb + MB_E + warp * 8, 8);
    asm volatile("fence.mbarrier_init.release.cluster;" ::: "memory");
  }
  __syncwarp();
  asm volatile("barrier.cluster.arrive.relaxed.aligned;" ::: "memory");
#pragma unroll
  for (int i = 0; i < 3; i++) if (wg * 3 + i < 8 || lane < 8) sts128(bs + B_TAB + (wg * 3 + i) * 512 + lane * 16, 0u, 0u, 0u, 0u);
  if (!has_ch && warp == 3) {
    const int nt = 4 - (rb & 1);
    if (lane == 0) mbar_expect(sb + MB_CS, nt * W_STAGE);
    __syncwarp();
    if (lane < nt) tma3d(sb + w2_slot(lane), &M.w1, 0, 64 * (4 * (rb & 1) + lane), 7 * fs, sb + MB_CS);
  }
  __syncwarp();
  unsigned char* wp = (unsigned char*)g_part + (size_t)cta * (3 * 16384) + tid * 16;
  uint32_t tag = 0;
  if (tid == 288) asm volatile("atom.relaxed.gpu.global.inc.u32 %0, [%1], 0x5fffffff;" : "=r"(tag) : "l"(&g_ticket) : "memory");
  if (warp < 7 && lane == 0) asm volatile("prefetch.tensormap [%0];" ::"l"(&M.x + warp + (warp == 6 ? max(fs - 5, 0) : 0)) : "memory");
  const uint32_t stg = bs + wg * STG_BYTES;
  const uint32_t kre = keep(stg + lane * 80), kua = keep(stg + 5120 + lane * 2), kaU = keep(stg + 5120 + (lane >> 3) * 16);
  const uint32_t kaA = keep(stg + (lane & 7) * 80 + (lane >> 4) * 2560 + (lane & 8) * 2);
  const uint32_t kaB = keep(stg + (lane & 7) * 80 + (lane & 8) * 320 + (lane & 16) + 32);
  const uint32_t kaC = keep(stg + ((lane & 7) + (lane >> 4) * 8) * 80 + (lane & 8) * 320 + 64);
  asm volatile("barrier.cluster.wait.aligned;" ::: "memory");
  float post = 0.f, k0 = 0.f, dt = 0.f, scale = 0.f, kacc[5][4];
  uint2 pla, pai, pcr, pci;
#pragma unroll
  for (int i = 0; i < 5; i++) { kacc[i][0] = 0.f; kacc[i][1] = 0.f; kacc[i][2] = 0.f; kacc[i][3] = 0.f; }
  if (has_ch) {
    dt = bf_round(ex2f(__uint_as_float(wdt << 16) * 1.4426950408889634f));
    const float dk = __uint_as_float(wdk << 16) * rcp_fast(2.f * dt);
    uint32_t mx2 = __vmaxu2(__vmaxu2(__vmaxu2(vcr.x & 0x7fff7fffu, vcr.y & 0x7fff7fffu), __vmaxu2(vcr.z & 0x7fff7fffu, vcr.w & 0x7fff7fffu)),
                            __vmaxu2(__vmaxu2(vci.x & 0x7fff7fffu, vci.y & 0x7fff7fffu), __vmaxu2(vci.z & 0x7fff7fffu, vci.w & 0x7fff7fffu)));
    uint32_t mxv = __reduce_max_sync(0xffffffffu, max(mx2 & 0xffffu, mx2 >> 16));
    const int e = min(max(max((int)(mxv >> 7), (int)((__float_as_uint(dk) >> 23) & 0xffu) - 9), 6), 254);
    scale = __uint_as_float((uint32_t)(259 - e) << 23);
    if (wg == 2) {
    post = 2.f * dt * __uint_as_float((uint32_t)(e - 5) << 23);
    k0 = ((bf_lo(vcr.x) + bf_hi(vcr.x)) + (bf_lo(vcr.y) + bf_hi(vcr.y))) + ((bf_lo(vcr.z) + bf_hi(vcr.z)) + (bf_lo(vcr.w) + bf_hi(vcr.w)));
    k0 = fmaf(dk, 1.f / 32.f, k0) * scale;
    }
    const uint32_t sh = (wg & 1) * 16;
    auto pick = [&](uint4 u) { const uint32_t lo = wg == 0 ? u.x : (wg == 1 ? u.y : u.w), hi = wg == 0 ? u.y : u.z; return make_uint2(__funnelshift_r(lo, hi, sh), hi >> sh); };
    pla = pick(vla); pai = pick(vai); pcr = pick(vcr); pci = pick(vci);
  }
  uint4 xv[7];
  if (wg == 2) {
    const uint4* src = (const uint4*)(P.x + (size_t)(rb * 128 + 8 * (4 * v + (lane >> 3)) + fs) * DM) + (lane & 7) + (__float_as_uint(k0) & blockIdx.y);
#pragma unroll
    for (int k = 0; k < 7; k++) xv[k] = ldg128(src + 8 * k);
  }
  auto issue_stage = [&](int t, int b) {
    if (v < 3 && lane == 0) {
      const uint32_t bar = sb + M_BAR + t * 8;
      mbar_expect(bar, v == 0 ? A_STAGE : (v == 1 ? 24576 : 4096));
      tma4d(sb + (v == 0 ? OFF_A + b * A_STAGE : OFF_W - 24576 + v * 24576 + b * W_STAGE), &M.x + v, v == 0 ? 64 * t : (v == 1 ? 0 : 224 * fs + ((fs & 1) ? 0 : 192)),
            v == 0 ? 0 : 64 * t, v == 1 ? (7 * fs + 1) >> 1 : 0, v == 0 ? 16 * rb : 0, bar);
    }
    __syncwarp();
  };
  if (!has_ch && wg < 2) {
    if (warp < 7) {
      float cs[4][4];
#pragma unroll
      for (int i = 0; i < 4; i++) { cs[i][0] = 0.f; cs[i][1] = 0.f; cs[i][2] = 0.f; cs[i][3] = 0.f; }
      mbar_wait(sb + MB_CS, 0);
      const uint32_t ca = warp * 4096 + (lane & 15) * 64 + ((((lane >> 4) & 1) ^ ((lane >> 1) & 3)) << 4);
#pragma unroll 1
      for (int t = 4 * (rb & 1); t < 16; t++) {
        const uint32_t a = sb + w2_slot(3 - (t >> 2)) + (t & 3) * 1024 + ca;
        uint32_t b[8];
        ldsm4t(b[0], b[1], b[2], b[3], a);
        ldsm4t(b[4], b[5], b[6], b[7], a ^ 32);
#pragma unroll
        for (int i = 0; i < 4; i++) ones_mma(cs[i], b[2 * i], b[2 * i + 1]);
      }
      bar_sync(BAR_INIT, 352);
      tag = lds32(sb + M_EPOCH);
      float2* dst = (float2*)(g_cs + (rb & 1) * FF + fs * 224 + warp * 32) + q;
#pragma unroll
      for (int i = 0; i < 4; i++) st_b64(lane < 4, dst + 4 * i, (__float_as_uint(cs[i][0]) & ~1u) | (tag & 1u), (__float_as_uint(cs[i][1]) & ~1u) | (tag >> 16));
      if (lane == 0) red_hint(g_done);
      asm volatile("fence.proxy.async.shared::cta;" ::: "memory");
    }
    bar_sync(BAR_K, 256);
    issue_stage(wg, wg);
    if (tid == 32) asm volatile("cp.async.bulk.prefetch.L2.global [%0], 100352;" ::"l"(P.w2 + (cta - 112) * 50176) : "memory");
    __syncwarp();
  }
#pragma unroll 1
  for (int b = has_ch ? wg >> 1 : 3; b < 3; b++) {
    {
      if (wg == 2) issue_stage(b - 1, b - 1);
      kgen_batch(kacc, bf_lo(pla.x), bf_lo(pai.x), bf_lo(pcr.x) * scale, bf_lo(pci.x) * scale, dt, kre, kua, kaA, kaB, kaC, kaU);
      pla.x = __funnelshift_r(pla.x, pla.y, 16); pai.x = __funnelshift_r(pai.x, pai.y, 16);
      pcr.x = __funnelshift_r(pcr.x, pcr.y, 16); pci.x = __funnelshift_r(pci.x, pci.y, 16);
    }
    if (wg == 2 && b == 2) bar_arrive(BAR_K, 384);
  }
  uint32_t kw[5][2];
#pragma unroll
  for (int i = 0; i < 5; i++) { kw[i][0] = pack_h2(kacc[i][0], kacc[i][1]); kw[i][1] = pack_h2(kacc[i][2], kacc[i][3]); }
  if (wg == 2) {
    const int st = tid - 256;
    {
      const int i = 4 * v + (lane >> 3), j = lane & 7;
#pragma unroll
      for (int o = 16; o; o >>= 1) k0 += __shfl_xor_sync(0xffffffffu, k0, o);
      float xf[56];
#pragma unroll
      for (int k = 0; k < 7; k++) {
        xf[8 * k] = bf_lo(xv[k].x); xf[8 * k + 1] = bf_hi(xv[k].x); xf[8 * k + 2] = bf_lo(xv[k].y); xf[8 * k + 3] = bf_hi(xv[k].y);
        xf[8 * k + 4] = bf_lo(xv[k].z); xf[8 * k + 5] = bf_hi(xv[k].z); xf[8 * k + 6] = bf_lo(xv[k].w); xf[8 * k + 7] = bf_hi(xv[k].w);
      }
      float s4[4] = {0.f, 0.f, 0.f, 0.f};
#pragma unroll
      for (int k = 0; k < 56; k++) s4[k & 3] += xf[k];
      float s0 = (s4[0] + s4[1]) + (s4[2] + s4[3]);
#pragma unroll
      for (int o = 1; o < 8; o <<= 1) s0 += __shfl_xor_sync(0xffffffffu, s0, o);
      const float mu = s0 * (1.f / DM);
      s4[0] = 0.f; s4[1] = 0.f; s4[2] = 0.f; s4[3] = 0.f;
#pragma unroll
      for (int k = 0; k < 56; k++) { xf[k] -= mu; s4[k & 3] = fmaf(xf[k], xf[k], s4[k & 3]); }
      s0 = (s4[0] + s4[1]) + (s4[2] + s4[3]);
#pragma unroll
      for (int o = 1; o < 8; o <<= 1) s0 += __shfl_xor_sync(0xffffffffu, s0, o);
      const float var = s0 * (1.f / DM);
      const float m1 = bf_round(mu);
      const float d1 = bf_round(sqrt_fast(bf_round(bf_round(var) + 1e-5f)));
      const float i1 = rcp_fast(d1);
      const float mu2 = (mu - m1) * i1;
      const float d2 = bf_round(sqrt_fast(bf_round(bf_round(var * i1 * i1) + 1e-5f)));
      const uint32_t tb = bs + 2 * STG_BYTES + (i & 3) * 1024 + (2 * v + (i & 1)) * 16 + j * 16;
#pragma unroll
      for (int k = 0; k < 7; k++)
        sts128(tb + k * 128, pack_h2(fmaf(xf[8 * k], i1, mu2), fmaf(xf[8 * k + 1], i1, mu2)), pack_h2(fmaf(xf[8 * k + 2], i1, mu2), fmaf(xf[8 * k + 3], i1, mu2)),
               pack_h2(fmaf(xf[8 * k + 4], i1, mu2), fmaf(xf[8 * k + 5], i1, mu2)), pack_h2(fmaf(xf[8 * k + 6], i1, mu2), fmaf(xf[8 * k + 7], i1, mu2)));
      if (tid == 288) { tag >>= 7; sts32(sb + M_EPOCH + 4, (tag + 1u) * 240u); tag = tag % 3u + 1u; sts32(sb + M_EPOCH, (tag & 1u) | ((tag & 2u) << 15)); }
      bar_sync(BAR_S, 128);
      if (!has_ch) bar_arrive(BAR_INIT, 352);
      tag = *(const volatile uint32_t*)(sm + M_EPOCH);
      st_b64(j == 0, &g_stats[cta * 16 + i], (__float_as_uint(fmaf(bf_round(mu2), d1, m1)) & ~1u) | (tag & 1u), (__float_as_uint(rcp_fast(d1 * d2)) & ~1u) | (tag >> 16));
      const int mi = lane >> 3, r = lane & 7, ri = 4 * (r >> 1) + 2 * (mi & 1) + (r & 1);
      const uint32_t la = sb + OFF_S + (ri >> 2) * S_BLK + 2 * STG_BYTES + (ri & 3) * 1024 + r * 16 + (14 * v + (mi >> 1)) * 16;
      __half* dst = g_xnT + (cta * DM + 112 * v) * 16 + lane * 4;
#pragma unroll
      for (int k = 0; k < 7; k++) {
        uint32_t r0, r1, r2, r3;
        ldsm4t(r0, r1, r2, r3, la + k * 32);
        st_b64(1, dst + 256 * k, r0, (r1 & 0xfffefffeu) | tag);
        st_b64(1, dst + 256 * k + 128, r2, (r3 & 0xfffefffeu) | tag);
      }
      bar_sync(BAR_S, 128);
      if (tid == 256) red_hint(g_done);
    }
    if (!has_ch) bar_sync(BAR_G1, 384);
    uint32_t R[8][4];
    {
      const int sd = min(st, 111), sc = (fs & 1) ? (sd < 96 ? sd + 16 : sd - 96) : sd;
      const uint32_t bb = __ldg((const uint32_t*)(P.b1 + fs * 224) + sc);
      const uint32_t b2w = __ldg((const uint32_t*)(P.b2 + oc0) + (st & 31));
      uint2 sv, ca, cb;
      uint32_t bad;
      int n = 0;
      auto fetch = [&]() {
        if (has_ch && lane == 0) {
          asm volatile("fence.proxy.async.shared::cta;" ::: "memory");
          if (v == 0) mbar_expect(sb + MB_CS, 16384);
          tma3d(bs + B_XT, &M.xt, cta * 64, 2 * v, 0, sb + MB_CS);
        }
        sv = ldr64(&g_stats[rb * 128 + (4 * (st & 1) + ((st >> 1) & 3)) * 16 + (st >> 3)]);
        ca = ldr64((const float2*)(g_cs + fs * 224) + sc); cb = ldr64((const float2*)(g_cs + FF + fs * 224) + sc);
      };
      if (!has_ch) {
        fetch();
      } else {
        const unsigned char* blk = sm + OFF_S + v * S_BLK;
        const uint32_t tb = bs + B_TAB, dump = tb + 4 * (T_B7 + 144);
        const uint32_t a0[2] = {tb + 4 * ((q & 1 ? T_A3 : T_A1) + 14 + (q >> 1) + 2 * g), tb + 4 * ((q & 1 ? T_A0 : T_A2) + 14 + ((q + 1) >> 1) + 2 * g)};
        const uint32_t a1[2] = {tb + 4 * (q < 2 ? T_A2 + 78 + q + 2 * g : (q == 2 ? T_B3 : T_B5) + 14 + g), tb + 4 * (q < 2 ? T_A4 + 14 + q + 2 * g : (q == 2 ? T_B3 : T_B5) + 46 + g)};
        const uint32_t u1 = q < 2 ? 64 : 32, h1 = q < 2 ? 10 : 6;
        const uint32_t a2 = tb + 4 * (T_B7 + 14 + 16 * q + g);
        const uint32_t s0 = lane == 31 ? tb + 4 * (T_A1 + 78) : (lane == 0 ? tb + 4 * (T_A0 + 14) : dump);
        const uint32_t s1 = lane == 31 ? tb + 4 * (T_BT + 14) : (lane == 29 ? tb + 4 * (T_A2 + 142) : dump);
        bar_sync(BAR_K2, 384);
        uint32_t w[5][2];
        {
          const uint4 a0 = ((const uint4*)blk)[lane], a1 = ((const uint4*)blk)[32 + lane], b0 = ((const uint4*)(blk + STG_BYTES))[lane], b1 = ((const uint4*)(blk + STG_BYTES))[32 + lane];
          const uint2 a2 = ((const uint2*)(blk + 1024))[lane], b2 = ((const uint2*)(blk + STG_BYTES + 1024))[lane];
          const uint32_t pa[10] = {a0.x, a0.y, a0.z, a0.w, a1.x, a1.y, a1.z, a1.w, a2.x, a2.y}, pb[10] = {b0.x, b0.y, b0.z, b0.w, b1.x, b1.y, b1.z, b1.w, b2.x, b2.y};
#pragma unroll
          for (int i = 0; i < 10; i++) w[i >> 1][i & 1] = hadd2(hadd2(pa[i], pb[i]), kw[i >> 1][i & 1]);
        }
        uint32_t cnt = ldr64(g_done).x;
#pragma unroll
        for (int k = 0; k < 8; k++) {
          const int mt = k >> 2, hh = (k >> 1) & 1, e = k & 1;
          uint32_t v0 = w[3 * mt][hh] >> (16 * e), v1 = w[3 * mt + 1][hh] >> (16 * e);
          sts16(a0[e] + (k >> 1) * 64, v0); sts16(a0[e] + (k >> 1) * 64 + 10, v0);
          sts16(a1[e] + (k >> 1) * u1, v1); sts16(a1[e] + (k >> 1) * u1 + h1, v1);
        }
        const uint32_t target = lds32(sb + M_EPOCH + 4);
        while ((int)(cnt - target) < 0 && ++n < SPIN) cnt = ldr64(g_done).x;
        n = 0;
        fetch();
#pragma unroll
        for (int k = 0; k < 4; k++) {
          const uint32_t v2 = __byte_perm(w[2][k >> 1], 0u, (k & 1) ? 0x3232 : 0x1010), ad = a2 + (k & 1) * 256 + (k >> 1) * 32;
          sts16(ad, v2); sts16(ad + 6, v2);
          asm volatile("{ .reg .pred p; .reg .b16 h, l; setp.ne.b32 p, %2, 0; mov.b32 {l, h}, %1; @p st.shared.b16 [%0], l; @p st.shared.b32 [%0+4], %1; @p st.shared.b16 [%0+10], l; }"
                       ::"r"(ad + 4 * (T_BT - T_B7)), "r"(v2), "r"(g & 1) : "memory");
        }
        const uint32_t l0 = lane == 0 ? pack_h2(k0, 0.f) : w[3][1] >> 16;
        sts16(s0, l0); sts16(s0 + 10, l0); sts16(s1, w[4][1] >> 16); sts16(s1 + h1, w[4][1] >> 16);
        __syncwarp();
      }
      while (true) {
        uint32_t bh = 0;
        if (has_ch) {
          mbar_wait(sb + MB_CS, n & 1);
          const uint32_t ra = OFF_S + B_XT + (lane >> 1) * 256 + (((2 * v) ^ (lane & 7)) << 4);
#pragma unroll
          for (int f = 0; f < 8; f++) {
            const uint4 u = *(const uint4*)(sm + ((ra + (f >> 1) * S_BLK + (f & 1) * 128) ^ ((f & 1) << 4)));
            R[f][0] = u.x; R[f][1] = u.y ^ tag; R[f][2] = u.z; R[f][3] = u.w ^ tag; bh |= R[f][1] | R[f][3];
          }
        }
        bad = (bh & 0x00010001u) | (((sv.x ^ tag) | (ca.x ^ tag) | (cb.x ^ tag) | (sv.y ^ (tag >> 16)) | (ca.y ^ (tag >> 16)) | (cb.y ^ (tag >> 16))) & 1u);
        asm volatile("{ .reg .pred p, q; setp.ne.b32 p, %0, 0; barrier.red.or.pred q, 1, 128, p; selp.b32 %0, 1, 0, q; }" : "+r"(bad) :: "memory");
        if (!retry(bad, n)) break;
        fetch();
      }
      __syncwarp();
      ((uint2*)(sm + M_ROW))[st] = make_uint2(sv.x & ~1u, sv.y & ~1u);
      ((uint32_t*)(sm + M_B2))[(st & 3) * 8 + ((st >> 2) & 7)] = pack_h2(0.5f * bf_lo(b2w), 0.5f * bf_hi(b2w));
      ((float4*)(sm + M_COL))[sd] = make_float4(__uint_as_float(ca.x & ~1u) + __uint_as_float(cb.x & ~1u), 0.25f * bf_lo(bb), __uint_as_float(ca.y & ~1u) + __uint_as_float(cb.y & ~1u), 0.25f * bf_hi(bb));
    }
    bar_arrive(BAR_STAT, 384);
    if (has_ch) {
      uint32_t Q[19][4];
#pragma unroll
      for (int f = 0; f < 8; f++) {
        uint32_t pv = __shfl_up_sync(0xffffffffu, R[f][3], 1);
        if (lane == 0) pv = 0;
#pragma unroll
        for (int k = 0; k < 4; k++) {
          Q[11 + f][k] = R[f][k];
          Q[3 + f][k] = __byte_perm(k ? R[f][k - 1] : pv, R[f][k], 0x5432);
          if (f >= 5) Q[f - 5][k] = k ? R[f][k - 1] : pv;
        }
      }
      uint32_t pa = bs + 16 + lane * 16;
#pragma unroll
      for (int f = 0; f < 12; f++) sts128(pa + B_P + f * PP, Q[7 + f][0], Q[7 + f][1], Q[7 + f][2], Q[7 + f][3]);
      if (lane < 20) sts128(bs + lane * PP, 0u, 0u, 0u, 0u);
      uint32_t B2[14][4], T3[12][4], V5[9][4], V7[8][4];
#pragma unroll
      for (int k = 0; k < 4; k++) {
#pragma unroll
        for (int f = 0; f < 14; f++) B2[f][k] = hadd2(Q[f][k], Q[f + 1][k]);
#pragma unroll
        for (int f = 0; f < 12; f++) T3[f][k] = hadd2(B2[f + 2][k], Q[f + 4][k]);
#pragma unroll
        for (int f = 0; f < 9; f++) V5[f][k] = hadd2(B2[f][k], T3[f][k]);
#pragma unroll
        for (int f = 0; f < 8; f++) V7[f][k] = hadd2(V5[f][k], B2[f + 5][k]);
      }
#pragma unroll
      for (int f = 0; f < 8; f++) sts128(pa + B_V3 + f * PP, T3[f + 4][0], T3[f + 4][1], T3[f + 4][2], T3[f + 4][3]);
      if (lane < 24) {
#pragma unroll
        for (int f = 0; f < 8; f++) sts128(bs + B_V5 + f * P5 + lane * 16, V5[f + 1][0], V5[f + 1][1], V5[f + 1][2], V5[f + 1][3]);
      }
      if (lane < 16) {
#pragma unroll
        for (int f = 0; f < 8; f++) sts128(bs + B_V7 + f * P7 + lane * 16, V7[f][0], V7[f][1], V7[f][2], V7[f][3]);
      }
      __syncwarp();
    }
    if (has_ch) {
      float acc[16][4];
#pragma unroll
      for (int i = 0; i < 16; i++) { acc[i][0] = 0.f; acc[i][1] = 0.f; acc[i][2] = 0.f; acc[i][3] = 0.f; }
      const int mi = lane >> 3, n = lane & 7;
      const uint32_t z = blockIdx.y;
      const uint32_t tA = bs + B_TAB + (14 + 2 * g - 4 * q) * 4, tB = bs + B_TAB + (g - 2 * q) * 4;
      const uint32_t kdiag = lds32(bs + B_TAB + 4 * (T_BT + 14)) & 0xffffu;
      const uint32_t lA = bs + ((n >> 1) + 4 * (mi & 1)) * PP + 16 + ((mi >> 1) + (n & 1)) * 16;
      const int r8 = 4 * (n & 1) + (n >> 1);
      const uint32_t lB = bs + r8 * PP + 16 + mi * 16;
      uint32_t tok = 0;
      {
        uint32_t a0 = g == 2 * q ? kdiag : (g == 2 * q + 1 ? kdiag << 16 : 0u);
        const uint32_t lX = lA + PP + (mi >> 1) * 16;
#pragma unroll
        for (int p = 0; p < 4; p++) {
          uint32_t b[4];
          ldsm4(b[0], b[1], b[2], b[3], lX + p * 64);
          hmma(acc[8 + 2 * p][0], acc[8 + 2 * p][1], acc[8 + 2 * p][2], acc[8 + 2 * p][3], a0, z, z + z, a0 ^ z, b[0], b[1]);
          hmma(acc[9 + 2 * p][0], acc[9 + 2 * p][1], acc[9 + 2 * p][2], acc[9 + 2 * p][3], a0, z, z + z, a0 ^ z, b[2], b[3]);
        }
      }
      conv_A<0, 5>(acc, tA + T_A0 * 4, lA + 4 * PP, z, tok);
      conv_A<0, 5>(acc, tA + T_A1 * 4, lA + 3 * PP, z, tok);
      conv_A<0, 5>(acc, tA + T_A3 * 4, lA + 1 * PP, z, tok);
      conv_A<0, 9>(acc, tA + T_A2 * 4, lA + 2 * PP, z, tok);
      conv_A<4, 5>(acc, tA + (T_A4 - 64) * 4, lA + B_V3, z, tok);
      conv_B<8, 8>(acc, tB + (T_B7 - 114) * 4, bs + B_V7 + r8 * P7 + mi * 16, z, tok);
      conv_B<8, 8>(acc, tB + (T_BT - 114) * 4, lB + B_P, z, tok);
      conv_B<4, 5>(acc, tB + (T_B5 - 50) * 4, bs + B_V5 + r8 * P5 + mi * 16, z, tok);
      conv_B<4, 5>(acc, tB + (T_B3 - 50) * 4, lB + B_V3, z, tok);
      uint32_t dep = 0;
#pragma unroll
      for (int i = 0; i < 16; i++) dep |= __float_as_uint(acc[i][0]);
      bar_arrive(BAR_PP + (dep & z), 256);
      post = __uint_as_float(__float_as_uint(post) | (dep & z));
      __syncwarp();
#pragma unroll
      for (int i = 0; i < 16; i++) {
        sts32(bs + i * 256 + lane * 4, (pack_h2(acc[i][0] * post, acc[i][2] * post) & 0xfffefffeu) | tag);
        sts32(bs + i * 256 + 128 + lane * 4, (pack_h2(acc[i][1] * post, acc[i][3] * post) & 0xfffefffeu) | tag);
      }
      asm volatile("fence.proxy.async.shared::cta;" ::: "memory");
      __syncwarp();
      if (lane == 0) {
        asm volatile("cp.async.bulk.global.shared::cta.bulk_group [%0], [%1], 4096;" ::"l"(g_y + (size_t)d * 1024), "r"(bs) : "memory");
        asm volatile("cp.async.bulk.commit_group;" ::: "memory");
        asm volatile("cp.async.bulk.wait_group.read 0;" ::: "memory");
      }
    } else {
      bar_arrive(BAR_PP, 256);
    }
    bar_sync(BAR_S, 128);
    if (st < 2) issue_w2(4 + st, sb, fs, M);
    {
      auto issue_rec = [&](int p, uint32_t dst) {
        const int bytes = fs < 6 ? 16384 : 8192;
        mbar_expect(sb + MB_R, bytes);
        asm volatile("cp.async.bulk.shared::cluster.global.mbarrier::complete_tx::bytes [%0], [%1], %3, [%2];"
                     ::"r"(dst), "l"((const unsigned char*)g_part + (size_t)(((cta & ~6) | ((((fs >> 1) - 1 - p) & 3) << 1)) * 3 + p) * 16384), "r"(sb + MB_R), "r"(bytes) : "memory");
      };
      if (st == 32) {
        mbar_wait(sb + MB_PASS, 0);
        issue_w2(6, sb, fs, M); issue_w2(7, sb, fs, M);
      }
      mbar_wait(sb + MB_PASS + 8, 0);
      uint32_t bad;
      int n = 0;
      do {
        if (st == 0) {
          mbar_expect(sb + MB_Y, 16384);
          tma2d(sb + OFF_YT, &M.y, 128 * rb, oc0, sb + MB_Y);
          tma2d(sb + OFF_YT + 8192, &M.y, 128 * rb + 64, oc0, sb + MB_Y);
          if (n == 0) issue_rec(0, sb);
        }
        mbar_wait(sb + MB_Y, n & 1);
        bad = 0;
        uint4 u[8];
#pragma unroll
        for (int i = 0; i < 8; i++) u[i] = ((const uint4*)(sm + OFF_YT))[i * 128 + st];
#pragma unroll
        for (int i = 0; i < 8; i++) {
          u[i].x ^= tag; u[i].y ^= tag; u[i].z ^= tag; u[i].w ^= tag;
          bad |= u[i].x | u[i].y | u[i].z | u[i].w;
          auto cv = [](uint32_t w) { __half2 t = *reinterpret_cast<__half2*>(&w); return pack_bf2(__low2float(t), __high2float(t)); };
          ((uint4*)(sm + OFF_YT))[i * 128 + st] = make_uint4(cv(u[i].x), cv(u[i].y), cv(u[i].z), cv(u[i].w));
        }
        asm volatile("fence.proxy.async.shared::cta;" ::: "memory");
        asm volatile("{ .reg .pred p, q; setp.ne.b32 p, %1, 0; barrier.red.or.pred q, 1, 128, p; selp.b32 %0, 1, 0, q; }" : "=r"(bad) : "r"(bad & 0x00010001u) : "memory");
      } while (retry(bad, n));
      bar_arrive(BAR_FIN, 256);
      bar_arrive(BAR_FIN + 1, 256);
    }
  } else {
    uint32_t h[56];
    {
      float acc[112];
      if (has_ch) {
        sts128(stg + lane * 16, kw[0][0], kw[0][1], kw[1][0], kw[1][1]);
        sts128(stg + 512 + lane * 16, kw[2][0], kw[2][1], kw[3][0], kw[3][1]);
        *(uint2*)(sm + (stg - sb) + 1024 + lane * 8) = make_uint2(kw[4][0], kw[4][1]);
        bar_arrive(BAR_K2, 384);
      }
      uint32_t A[4][4];
      const uint32_t xr = sb + OFF_A + (warp * 16 + (lane & 15)) * 128, xs = (lane >> 4) ^ (lane & 7);
      const uint32_t xk[4] = {xr + (xs << 4), xr + ((xs ^ 2) << 4), xr + ((xs ^ 4) << 4), xr + ((xs ^ 6) << 4)};
      const uint32_t dw = ((sb + OFF_W) & 0x3ffffu) >> 4;
      mbar_wait(sb + M_BAR, 0);
      ldsm4(A[0][0], A[0][1], A[0][2], A[0][3], xk[0]);
      if (has_ch) bar_sync(BAR_K, 384);
#pragma unroll
      for (int kb = 0; kb < 7; kb++) {
#pragma unroll
        for (int k = 0; k < 4; k++) {
          constexpr int WS = W_STAGE / 16;
          const int n = (k + 1) & 3, s = kb % 3, sn = (kb + (k == 3)) % 3;
          if (k == 3 && kb < 6) mbar_wait(sb + M_BAR + kb * 8 + 8, 0);
          if (k == 1 && kb > 0) wg_wait1(); else if (kb > 0 || k == 3) wg_wait2();
          if (kb < 6 || k < 3) ldsm4(A[n][0], A[n][1], A[n][2], A[n][3], xk[n] + sn * A_STAGE);
          if (k == 1 && kb > 0 && lane == 0) mbar_arrive(sb + MB_E + (kb - 1) * 8);
          wg_fence();
          wgmma_rs_n192(acc, A[k][0], A[k][1], A[k][2], A[k][3], desc64(dw + (s * WS + k * 128 + 0x2000000), 0x40000040u), k | kb);
          wgmma_rs_n32(acc, A[k][0], A[k][1], A[k][2], A[k][3], desc64(dw + (s * WS + 1536 + k * 64 + 0x1000000), 0x80000020u), k | kb);
          wg_commit();
          if (k == (kb > 0) && wg == (kb & 1)) {
            if (kb > 0) mbar_wait(sb + MB_E + (kb - 1) * 8, 0);
            if (kb < 5) issue_stage(kb + 2, (kb + 2) % 3);
            else { if ((tid & 127) == 0) issue_w2(kb - 5, sb, fs, M); __syncwarp(); }
          }
        }
      }
      wg_wait0();
      fence_regs(acc);
      if (!has_ch) bar_arrive(BAR_G1, 384);
      uint32_t peer;
      asm("mapa.shared::cluster.u32 %0, %1, %2;" : "=r"(peer) : "r"(sb), "r"((fs & 1) ^ 1));
      if (lane == 0) asm volatile("mbarrier.arrive.relaxed.cluster.shared::cluster.b64 _, [%0];" ::"r"(peer + MB_FREE) : "memory");
      bar_sync(BAR_STAT, 384);
      if (tid == 0) { mbar_expect(sb + MB_X, A_STAGE); tma4d(sb + OFF_XT, &M.x, oc0, 0, 0, 16 * rb, sb + MB_X); }
      __syncwarp();
      mbar_wait(sb + MB_FREE, 0);
      const int row = wg * 64 + v * 16 + g;
      float2 st0 = ((const float2*)(sm + M_ROW))[row], st1 = ((const float2*)(sm + M_ROW))[row + 8];
      float r0 = 0.25f * st0.y, c0 = -r0 * st0.x, r1 = 0.25f * st1.y, c1 = -r1 * st1.x;
      constexpr int PF = 4;
      float4 cvs[28 + PF];
#pragma unroll
      for (int i = 0; i < PF; i++) cvs[i] = lds128f(sb + M_COL + 64 * i + 16 * q);
#pragma unroll
      for (int i = 0; i < 28; i++) {
        if (i + PF < 28) cvs[i + PF] = lds128f(sb + M_COL + 64 * (i + PF) + 16 * q);
        const float4 cv = cvs[i];
        float w[4] = {fmaf(r0, acc[4 * i], fmaf(c0, cv.x, cv.y)), fmaf(r0, acc[4 * i + 1], fmaf(c0, cv.z, cv.w)),
                      fmaf(r1, acc[4 * i + 2], fmaf(c1, cv.x, cv.y)), fmaf(r1, acc[4 * i + 3], fmaf(c1, cv.z, cv.w))};
        h[2 * i] = gelu2(w[0], w[1]);
        h[2 * i + 1] = gelu2(w[2], w[3]);
        if (i == 27) {
#pragma unroll
          for (int e = 0; e < 4; e++)
            asm volatile("st.async.weak.shared::cluster.mbarrier::complete_tx::bytes.b32 [%0], %1, [%2];"
                         ::"r"(peer + OFF_HL + warp * 512 + (e & 1) * 256 + (e >> 1) * 128 + lane * 4), "r"(h[52 + e]), "r"(peer + MB_H));
        } else if (i & 1)
          asm volatile("st.async.weak.shared::cluster.mbarrier::complete_tx::bytes.v4.b32 [%0], {%1,%2,%3,%4}, [%5];"
                       ::"r"(peer + OFF_H + (i >> 1) * 4096 + tid * 16), "r"(h[2 * i - 2]), "r"(h[2 * i - 1]), "r"(h[2 * i]), "r"(h[2 * i + 1]), "r"(peer + MB_H));
      }
    }
    uint32_t hp[52];
    mbar_wait(sb + MB_H, 0);
#pragma unroll
    for (int k = 0; k < 13; k++) { uint4 u = ((const uint4*)(sm + OFF_H))[k * 256 + tid]; hp[4 * k] = u.x; hp[4 * k + 1] = u.y; hp[4 * k + 2] = u.z; hp[4 * k + 3] = u.w; }
    tag = *(const volatile uint32_t*)(sm + M_EPOCH);
    asm volatile("fence.proxy.async.shared::cta;" ::: "memory");
    bar_sync(BAR_C, 256);
    if (tid < 2) issue_w2(2 + tid, sb, fs, M);
    const uint64_t dl = mkdesc(sb + OFF_HL + wg * 2048, 128, 256, 0);
    __syncwarp();
    float o[32];
#pragma unroll
    for (int i = 0; i < 32; i++) o[i] = 0.f;
    auto rec_ptr = [&](int p) { return (const unsigned char*)g_part + (size_t)(((cta & ~6) | ((((fs >> 1) - 1 - p) & 3) << 1)) * 3 + p) * 16384; };
#pragma unroll 1
    for (int p = 0;; p++) {
      const bool half = (((fs >> 1) + 1 + p) & 3) == 3;
      const uint32_t ks = 128u;
      const uint32_t up = 0x10000u + (half ? (fs & 1) * 4u : 0u);
      const uint32_t d0 = (((sb + w2_slot(2 * p)) & 0x3ffffu) >> 4) + up, d1 = (((sb + w2_slot(2 * p + 1)) & 0x3ffffu) >> 4) + up;
      const uint32_t d0a = d0 + ((fs & 1) ? 2 * ks : 0u), d0b = d0 + ((fs & 1) ? 0u : 12 * ks), d1a = d1 + ((fs & 1) ? 0u : 2 * ks), d1b = d1 + ((fs & 1) ? 12 * ks : 0u);
      mbar_wait(sb + MB_W2 + 16 * p, 0);
      mbar_wait(sb + MB_W2 + 16 * p + 8, 0);
      bar_sync(BAR_PP + wg, 256);
      gemm2_pass(o, h, hp, desc64(d0a, 0x40000040u), desc64(d0b, 0x40000040u), desc64(d1a, 0x40000040u), desc64(d1b, 0x40000040u), dl, half, wg == 0 || p < 3 ? BAR_PP + (wg ^ 1) : 0);
      if (p == 3) break;
      wg_wait0();
      fence_regs(o);
#pragma unroll
      for (int k = 0; k < 4; k++)
        st_b128(k < 2 || !half, wp + k * 4096, pack_h2(o[8 * k], o[8 * k + 1]), pack_h2(o[8 * k + 2], o[8 * k + 3]), pack_h2(o[8 * k + 4], o[8 * k + 5]), (pack_h2(o[8 * k + 6], o[8 * k + 7]) & 0xfffefffeu) | tag);
      wp += 16384;
      if (p < 2 && lane == 0) mbar_arrive(sb + MB_PASS + p * 8);
    }
    uint32_t rec[3][16];
    const int full = fs < 6;
    const unsigned char *rp1 = rec_ptr(1) + tid * 16, *rp2 = rec_ptr(2) + tid * 16;
    const int ro = full ? 8192 : 0;
    mbar_wait(sb + MB_X, 0); mbar_wait(sb + MB_R, 0); bar_sync(BAR_FIN + wg, 256);
    wg_wait0();
    fence_regs(o);
    ld_rec(rec[2], rp2, rp2 + ro);
    ld_rec(rec[1], rp1, rp1 + ro);
#pragma unroll
    for (int k = 0; k < 4; k++) { uint4 u = ((const uint4*)sm)[k * 256 + tid]; rec[0][4 * k] = u.x; rec[0][4 * k + 1] = u.y; rec[0][4 * k + 2] = u.z; rec[0][4 * k + 3] = u.w; }
    const uint32_t xa = sb + OFF_XT + (warp * 16 + (lane & 15)) * 128, xo = (lane >> 4) ^ (lane & 7);
    const uint32_t ya = sb + OFF_YT + wg * 8192 + ((lane >> 4) * 8 + (lane & 7)) * 128 + (((2 * v + ((lane >> 3) & 1)) ^ (lane & 7)) << 4);
    uint32_t sv[16], xw[16];
#pragma unroll
    for (int i = 0; i < 4; i++) {
      ldsm4t(sv[4 * i], sv[4 * i + 1], sv[4 * i + 2], sv[4 * i + 3], ya + i * 2048);
      ldsm4(xw[4 * i], xw[4 * i + 1], xw[4 * i + 2], xw[4 * i + 3], xa + ((xo ^ (2 * i)) << 4));
    }
    const uint4 b0 = ((const uint4*)(sm + M_B2))[2 * q], b1 = ((const uint4*)(sm + M_B2))[2 * q + 1];
    const uint32_t bb[8] = {b0.x, b0.y, b0.z, b0.w, b1.x, b1.y, b1.z, b1.w};
    {
      const uint32_t m2 = full ? 0x00010001u : 0u;
      int n = 0;
      while ((rec_bad(rec[0], tag, m2) | rec_bad(rec[1], tag, m2) | rec_bad(rec[2], tag, m2)) != 0u && ++n < SPIN) {
#pragma unroll
        for (int p = 0; p < 3; p++) ld_rec(rec[p], rec_ptr(p) + tid * 16, rec_ptr(p) + tid * 16 + ro);
      }
      __syncwarp();
#pragma unroll
      for (int k = 0; k < 12; k++) rec[k >> 2][4 * (k & 3) + 3] ^= tag;
    }
    {
#pragma unroll
      for (int hf = 0; hf < 2; hf++) {
        if (hf == 0 || full) {
          uint32_t res[8];
#pragma unroll
          for (int k = 0; k < 8; k++) {
            const int i = 8 * hf + k;
            uint32_t su = hadd2(hadd2(rec[0][i], bb[i >> 1]), hadd2(rec[1][i], rec[2][i]));
            __half2 hv = *reinterpret_cast<__half2*>(&su);
            float h0 = __low2float(hv) + o[2 * i], h1 = __high2float(hv) + o[2 * i + 1];
            asm("fma.rn.bf16x2 %0, %1, %2, %3;" : "=r"(res[k]) : "r"(sv[i]), "r"(pack_bf2(fmaf(h0, tanhf_fast(h0), h0), fmaf(h1, tanhf_fast(h1), h1))), "r"(xw[i]));
          }
#pragma unroll
          for (int k = 0; k < 2; k++)
            asm volatile("stmatrix.sync.aligned.m8n8.x4.shared.b16 [%0], {%1,%2,%3,%4};" ::"r"(xa + ((xo ^ (4 * hf + 2 * k)) << 4)), "r"(res[4 * k]), "r"(res[4 * k + 1]), "r"(res[4 * k + 2]), "r"(res[4 * k + 3]) : "memory");
        }
      }
      asm volatile("fence.proxy.async.shared::cta;" ::: "memory");
      __syncwarp();
      if (lane == 0) {
        asm volatile("cp.async.bulk.tensor.4d.global.shared::cta.bulk_group [%0, {%2, %4, %4, %3}], [%1];"
                     ::"l"(&M.out[full ? 0 : fs - 5]), "r"(sb + OFF_XT + warp * 2048), "r"(oc0), "r"(16 * rb + 2 * warp), "r"(0) : "memory");
        asm volatile("cp.async.bulk.commit_group;" ::: "memory");
        asm volatile("cp.async.bulk.wait_group.read 0;" ::: "memory");
      }
    }
  }
}

typedef CUresult (*EncodeFn)(CUtensorMap*, CUtensorMapDataType, cuuint32_t, void*, const cuuint64_t*, const cuuint64_t*, const cuuint32_t*,
                             const cuuint32_t*, CUtensorMapInterleave, CUtensorMapSwizzle, CUtensorMapL2promotion, CUtensorMapFloatOOBfill);

}

extern "C" void kernel_launch(void* const* d_in, const int* in_sizes, int n_in, void* d_out, int out_size) {
  (void)in_sizes; (void)n_in; (void)out_size;
  static EncodeFn enc = nullptr;
  if (!enc) {
    void* fn = nullptr;
    cudaDriverEntryPointQueryResult qr;
    cudaGetDriverEntryPoint("cuTensorMapEncodeTiled", &fn, cudaEnableDefault, &qr);
    enc = (EncodeFn)fn;
    cudaFuncSetAttribute(fused_kernel, cudaFuncAttributeMaxDynamicSharedMemorySize, SMEM_BYTES);
  }
  typedef const __nv_bfloat16* bp;
  Params P;
  P.x = (bp)d_in[0]; P.logA = (bp)d_in[1]; P.Aim = (bp)d_in[2]; P.Cre = (bp)d_in[3]; P.Cim = (bp)d_in[4];
  P.logdt = (bp)d_in[5]; P.Dskip = (bp)d_in[6]; P.b1 = (bp)d_in[9]; P.w2 = (bp)d_in[10]; P.b2 = (bp)d_in[11];
  Maps M;
  void *yp = nullptr, *xp = nullptr;
  cudaGetSymbolAddress(&yp, g_y);
  auto mk = [&](CUtensorMap* m, int rank, void* base, std::initializer_list<cuuint64_t> dims, std::initializer_list<cuuint64_t> str,
                std::initializer_list<cuuint32_t> box, CUtensorMapSwizzle sw) {
    const cuuint32_t es[4] = {1, 1, 1, 1};
    enc(m, CU_TENSOR_MAP_DATA_TYPE_BFLOAT16, rank, base, dims.begin(), str.begin(), box.begin(), es, CU_TENSOR_MAP_INTERLEAVE_NONE, sw,
        CU_TENSOR_MAP_L2_PROMOTION_L2_128B, CU_TENSOR_MAP_FLOAT_OOB_FILL_NONE);
  };
  mk(&M.x, 4, d_in[0], {DM, 2, 4, SEQ / 8}, {4 * DM * 2, DM * 2, 8 * DM * 2}, {64, 2, 4, 16}, CU_TENSOR_MAP_SWIZZLE_128B);
  mk(&M.w1, 3, d_in[8], {32, DM, FF / 32}, {FF * 2, 64}, {32, 64, 7}, CU_TENSOR_MAP_SWIZZLE_64B);
  mk(&M.w1a, 4, d_in[8], {64, DM, FF / 64, 1}, {FF * 2, 128, FF * DM * 2}, {64, 64, 3, 1}, CU_TENSOR_MAP_SWIZZLE_128B);
  mk(&M.w1h, 4, d_in[8], {FF, DM, 1, 1}, {FF * 2, FF * DM * 2, FF * DM * 2}, {32, 64, 1, 1}, CU_TENSOR_MAP_SWIZZLE_64B);
  mk(&M.w2a, 2, d_in[10], {DM, FF}, {DM * 2}, {64, 224}, CU_TENSOR_MAP_SWIZZLE_128B);
  for (int i = 0; i < 3; i++)
    mk(&M.out[i], 4, d_out, {(cuuint64_t)(i == 0 ? DM : 192 + 32 * i), 2, 4, SEQ / 8}, {4 * DM * 2, DM * 2, 8 * DM * 2}, {64, 2, 4, 2}, CU_TENSOR_MAP_SWIZZLE_128B);
  cudaGetSymbolAddress(&xp, g_xnT);
  mk(&M.xt, 3, xp, {DM * 16, 8, 16}, {DM * 32, 8 * DM * 32}, {64, 2, 16}, CU_TENSOR_MAP_SWIZZLE_128B);
  mk(&M.y, 2, yp, {SEQ, DM}, {SEQ * 2}, {64, 64}, CU_TENSOR_MAP_SWIZZLE_128B);
  fused_kernel<<<NCTA, NTHR, SMEM_BYTES, cudaStreamPerThread>>>(P, M);
}
```
